```python
import torch

def _softmax(x, axis=-1):
    return torch.softmax(x, dim=axis)
def _gelu(x):
    return torch.nn.functional.gelu(x, approximate="tanh")
def _silu(x):
    return torch.nn.functional.silu(x)
def _sigmoid(x):
    return torch.sigmoid(x)
def _layernorm(x, axis=-1, eps=1e-5):
    m = x.mean(dim=axis, keepdim=True)
    v = x.var(dim=axis, keepdim=True, unbiased=False)
    return (x - m) / torch.sqrt(v + eps)
def _scatter_add(tgt, idx, src, axis=0):
    return tgt.clone().index_add_(axis, idx, src)
def _segment_sum(src, seg, n):
    out = torch.zeros((n,) + src.shape[1:], dtype=src.dtype)
    return out.index_add_(0, seg, src)
def _pad(x, pw):
    flat = tuple(v for pair in reversed(pw) for v in pair)
    return torch.nn.functional.pad(x, flat)

kernel_name = 'gated_mix__sliding_block_cached__gqa_block_cached__decode'

def setup_inputs():

    _w = (lambda a: (lambda t: t.to(torch.bfloat16) if t.is_floating_point() else t)(torch.as_tensor(a)))
    def _A_setup():
        B, Sq, D = 1, 1, 448
        Hq, Hkv, Sk, Dh = 16, 8, 8192, 256
        assert Hq % Hkv == 0, (Hq, Hkv)
        return {
            "x": _w((lambda *s: torch.randn(*s, dtype=torch.bfloat16) * 0.05)(B, Sq, D)),
            "k_cache": _w((lambda *s: torch.randn(*s, dtype=torch.bfloat16) * 3.2)(B, Hkv, Sk, Dh)),
            "v_cache": _w((lambda *s: torch.randn(*s, dtype=torch.bfloat16) * 0.05)(B, Hkv, Sk, Dh)),
            "wq": _w((lambda *s: torch.randn(*s, dtype=torch.bfloat16) * 3.2)(D, Hq * Dh) * (D ** -0.5)),
            "wo": _w((lambda *s: torch.randn(*s, dtype=torch.bfloat16) * 0.05)(Hq * Dh, D) * ((Hq * Dh) ** -0.5)),
        }
    _A_in = _A_setup()

    def _B_setup():
        B, Sq, D = 1, 1, 448
        Hq, Hkv, Sk, Dh = 16, 8, 8192, 256
        assert Hq % Hkv == 0, (Hq, Hkv)
        return {
            "x": _w((lambda *s: torch.randn(*s, dtype=torch.bfloat16) * 0.05)(B, Sq, D)),
            "k_cache": _w((lambda *s: torch.randn(*s, dtype=torch.bfloat16) * 3.2)(B, Hkv, Sk, Dh)),
            "v_cache": _w((lambda *s: torch.randn(*s, dtype=torch.bfloat16) * 0.05)(B, Hkv, Sk, Dh)),
            "wq": _w((lambda *s: torch.randn(*s, dtype=torch.bfloat16) * 3.2)(D, Hq * Dh) * (D ** -0.5)),
            "wo": _w((lambda *s: torch.randn(*s, dtype=torch.bfloat16) * 0.05)(Hq * Dh, D) * ((Hq * Dh) ** -0.5)),
        }
    _B_in = _B_setup()

    return {
        "A_x": _A_in["x"],
        "A_k_cache": _A_in["k_cache"],
        "A_v_cache": _A_in["v_cache"],
        "A_wq": _A_in["wq"],
        "A_wo": _A_in["wo"],
        "B_x": _B_in["x"],
        "B_k_cache": _B_in["k_cache"],
        "B_v_cache": _B_in["v_cache"],
        "B_wq": _B_in["wq"],
        "B_wo": _B_in["wo"],
        "gate_w": _w((lambda *s: torch.randn(*s, dtype=torch.bfloat16) * 0.1)(448) * 16.0),
    }

def reference(A_x, A_k_cache, A_v_cache, A_wq, A_wo, B_x, B_k_cache, B_v_cache, B_wq, B_wo, gate_w):
    def _A_ref(x, k_cache, v_cache, wq, wo):
        B, Sq, D = x.shape
        Hq, Dh = 16, 256
        Hkv, Sk = k_cache.shape[1], k_cache.shape[2]
        W = min(4096, max(256, Sk // 4))
        rep = Hq // Hkv
        q = (lambda x, *d: x.permute(*d))((x @ wq).reshape(B, Sq, Hq, Dh), 0, 2, 1, 3)
        k = (lambda x, n, axis: torch.repeat_interleave(x, n, dim=axis))(k_cache[:, :, Sk - W:, :], rep, axis=1)
        v = (lambda x, n, axis: torch.repeat_interleave(x, n, dim=axis))(v_cache[:, :, Sk - W:, :], rep, axis=1)
        scores = torch.einsum("bhqd,bhkd->bhqk", q, k) * (Dh ** -0.5)
        p = _softmax(scores, axis=-1)
        o = torch.einsum("bhqk,bhkd->bhqd", p, v)
        return (lambda x, *d: x.permute(*d))(o, 0, 2, 1, 3).reshape(B, Sq, Hq * Dh) @ wo

    def _B_ref(x, k_cache, v_cache, wq, wo):
        B, Sq, D = x.shape
        Hq, Dh = 16, 256
        Hkv = k_cache.shape[1]
        rep = Hq // Hkv
        q = (lambda x, *d: x.permute(*d))((x @ wq).reshape(B, Sq, Hq, Dh), 0, 2, 1, 3)
        k = (lambda x, n, axis: torch.repeat_interleave(x, n, dim=axis))(k_cache, rep, axis=1)
        v = (lambda x, n, axis: torch.repeat_interleave(x, n, dim=axis))(v_cache, rep, axis=1)
        scores = torch.einsum("bhqd,bhkd->bhqk", q, k) * (Dh ** -0.5)
        p = _softmax(scores, axis=-1)
        o = torch.einsum("bhqk,bhkd->bhqd", p, v)
        return (lambda x, *d: x.permute(*d))(o, 0, 2, 1, 3).reshape(B, Sq, Hq * Dh) @ wo

    x = A_x
    g = _sigmoid((x * gate_w).sum(-1, keepdims=True))
    a = _A_ref(x, A_k_cache, A_v_cache, A_wq, A_wo)
    b = _B_ref(x, B_k_cache, B_v_cache, B_wq, B_wo)
    return g * a + (1 - g) * b
```

```cpp
#include <cuda_runtime.h>
#include <cuda_bf16.h>
#include <stdint.h>

#define NS 10
#define WIN 3
#define WO_LEAD 2
#define WO_STEP 0
#define PACE0 4
#define PACE1 8
#define PACE2 12

namespace {

constexpr int DM = 448;
constexpr int SK = 8192;
constexpr int WA = 2048;
constexpr int NCTA = 128;
constexpr int TILE = 16384;
constexpr int NA = 4, NB = 16;
constexpr int NKV = 2 * (NA + NB);
constexpr int NT = NKV + 4;
constexpr int WOT = 16 * DM * 2;
constexpr int NTHREADS = 320;
constexpr int NRED = DM / 4;
constexpr uint32_t SPIN_LIMIT = 1u << 22;

constexpr int OFF_Q    = NS * TILE;
constexpr int OFF_S    = OFF_Q + 2048;
constexpr int OFF_P    = OFF_S + 4096;
constexpr int OFF_QR   = OFF_P + 2048;
constexpr int OFF_M    = OFF_QR + 2048;
constexpr int OFF_L    = OFF_M + 128;
constexpr int OFF_O    = OFF_L + 128;
constexpr int OFF_TAG  = OFF_O + 256;
constexpr int OFF_BAR  = OFF_TAG + 16;
constexpr int B_FULL = 0, B_EMPTY = NT, B_PACE = 2 * NT, B_QPART = B_PACE + 3, B_QREADY = B_QPART + 1,
              B_ML = B_QREADY + 1  , B_MLSEEN = B_ML + 2, B_VDONE = B_MLSEEN + 1  ,
              B_OREADY = B_VDONE + 2  , NBAR = B_OREADY + 2;
constexpr int SMEM_BYTES = OFF_BAR + NBAR * 8;

struct Params {
    const __nv_bfloat16 *x, *gw;
    const char *k[2], *v[2], *wq[2], *wo[2];
    __nv_bfloat16* out;
};

__device__ unsigned int g_epoch;
__device__ ulonglong2 g_q[8][256];
__device__ ulonglong2 g_ml[8][2][16][2];
__device__ ulonglong2 g_o[8][16][16][16];
__device__ ulonglong2 g_y[NRED][NCTA][2];
#define STAMP(i)

__device__ __forceinline__ void mbar_init(uint32_t bar, uint32_t cnt) {
    asm volatile("mbarrier.init.shared::cta.b64 [%0], %1;" ::"r"(bar), "r"(cnt) : "memory");
}
__device__ __forceinline__ void mbar_arrive(uint32_t bar) {
    asm volatile("mbarrier.arrive.shared::cta.b64 _, [%0];" ::"r"(bar) : "memory");
}
__device__ __forceinline__ void mbar_expect_tx(uint32_t bar, uint32_t bytes) {
    asm volatile("mbarrier.arrive.expect_tx.shared::cta.b64 _, [%0], %1;" ::"r"(bar), "r"(bytes) : "memory");
}
__device__ __forceinline__ void mbar_wait(uint32_t bar) {
    uint32_t n = 0;
    while (true) {
        uint32_t ok;
        asm volatile("{\n.reg .pred p;\nmbarrier.try_wait.parity.shared::cta.b64 p, [%1], 0;\nselp.u32 %0, 1, 0, p;\n}\n"
                     : "=r"(ok) : "r"(bar) : "memory");
        if (ok) break;
        if (++n > SPIN_LIMIT) __trap();
    }
}
__device__ __forceinline__ void bulk_load(uint32_t dst, const void* src, uint32_t bytes, uint32_t bar, uint64_t pol) {
    asm volatile("cp.async.bulk.shared::cluster.global.mbarrier::complete_tx::bytes.L2::cache_hint [%0], [%1], %2, [%3], %4;"
                 ::"r"(dst), "l"(src), "r"(bytes), "r"(bar), "l"(pol) : "memory");
}
__device__ __forceinline__ void ldsm4(uint32_t (&r)[4], uint32_t a) {
    asm volatile("ldmatrix.sync.aligned.m8n8.x4.shared.b16 {%0,%1,%2,%3}, [%4];"
                 : "=r"(r[0]), "=r"(r[1]), "=r"(r[2]), "=r"(r[3]) : "r"(a) : "memory");
}
__device__ __forceinline__ void ldsm4t(uint32_t (&r)[4], uint32_t a) {
    asm volatile("ldmatrix.sync.aligned.m8n8.x4.trans.shared.b16 {%0,%1,%2,%3}, [%4];"
                 : "=r"(r[0]), "=r"(r[1]), "=r"(r[2]), "=r"(r[3]) : "r"(a) : "memory");
}
__device__ __forceinline__ void mma16816(float (&c)[4], uint32_t a0, uint32_t a1, uint32_t a2, uint32_t a3,
                                         uint32_t b0, uint32_t b1) {
    asm volatile("mma.sync.aligned.m16n8k16.row.col.f32.bf16.bf16.f32 {%0,%1,%2,%3}, {%4,%5,%6,%7}, {%8,%9}, {%0,%1,%2,%3};"
                 : "+f"(c[0]), "+f"(c[1]), "+f"(c[2]), "+f"(c[3])
                 : "r"(a0), "r"(a1), "r"(a2), "r"(a3), "r"(b0), "r"(b1));
}
__device__ __forceinline__ float bf_lo(uint32_t v) { return __uint_as_float(v << 16); }
__device__ __forceinline__ float bf_hi(uint32_t v) { return __uint_as_float(v & 0xffff0000u); }
__device__ __forceinline__ uint32_t pack_bf2(float lo, float hi) {
    uint32_t r;
    asm("cvt.rn.bf16x2.f32 %0, %1, %2;" : "=r"(r) : "f"(hi), "f"(lo));
    return r;
}
__device__ __forceinline__ float round_bf(float v) { return bf_lo(pack_bf2(v, 0.f)); }
__device__ __forceinline__ float ex2(float v) {
    float r;
    asm("ex2.approx.ftz.f32 %0, %1;" : "=f"(r) : "f"(v));
    return r;
}
__device__ __forceinline__ void put2(void* p, uint32_t a, uint32_t b, uint32_t tag) {
    asm volatile("{\n.reg .b64 x, y;\nmov.b64 x, {%1, %3};\nmov.b64 y, {%2, %3};\n"
                 "st.relaxed.gpu.global.v2.b64 [%0], {x, y};\n}\n" ::"l"(p), "r"(a), "r"(b), "r"(tag) : "memory");
}
__device__ __forceinline__ void put1(void* p, uint32_t a, uint32_t tag) {
    asm volatile("{\n.reg .b64 x;\nmov.b64 x, {%1, %2};\nst.relaxed.gpu.global.b64 [%0], x;\n}\n"
                 ::"l"(p), "r"(a), "r"(tag) : "memory");
}
__device__ __forceinline__ uint4 get2(const void* p) {
    uint4 r;
    asm volatile("{\n.reg .b64 x, y;\nld.relaxed.gpu.global.v2.b64 {x, y}, [%4];\n"
                 "mov.b64 {%0, %1}, x;\nmov.b64 {%2, %3}, y;\n}\n"
                 : "=r"(r.x), "=r"(r.y), "=r"(r.z), "=r"(r.w) : "l"(p) : "memory");
    return r;
}
__device__ __forceinline__ void gather8(uint4 (&v)[8], const char* p, uint32_t tag) {
#pragma unroll
    for (int k = 0; k < 8; k++) v[k].y = v[k].w = tag + 1;
    uint32_t n = 0;
    while (true) {
#pragma unroll
        for (int k = 0; k < 8; k++)
            if (v[k].y != tag || v[k].w != tag) v[k] = get2(p + 512 * k);
        bool ok = true;
#pragma unroll
        for (int k = 0; k < 8; k++) ok = ok && v[k].y == tag && v[k].w == tag;
        if (__all_sync(0xffffffffu, ok)) break;
        if (++n > SPIN_LIMIT) __trap();
    }
}

constexpr float SCALE_LOG2E = 0.0625f * 1.4426950408889634f;

__global__ void __launch_bounds__(NTHREADS, 1) gated_mix_decode_kernel(const __grid_constant__ Params p) {
    extern __shared__ __align__(1024) char smem[];
    const uint32_t sb = (uint32_t)__cvta_generic_to_shared(smem);
    const uint32_t bars = sb + OFF_BAR;
    const int tid = threadIdx.x, warp = tid >> 5, lane = tid & 31;
    const int cta = blockIdx.x, head = cta >> 4, j = cta & 15;

    if (warp < 8) {
        if (tid == 0) STAMP(0);
        uint4 w[14];
        uint32_t xr[14];
        {
            uint64_t pol;
            asm volatile("createpolicy.fractional.L2::evict_first.b64 %0, 1.0;" : "=l"(pol));
            const char* wq = p.wq[j >> 3] + (size_t)(tid >> 3) * 8192 + (head * 512 + (j & 7) * 64) * 2 + (tid & 7) * 16;
#pragma unroll
            for (int i = 0; i < 14; i++)
                asm volatile("ld.global.nc.L1::no_allocate.L2::cache_hint.v4.u32 {%0,%1,%2,%3}, [%4], %5;"
                             : "=r"(w[i].x), "=r"(w[i].y), "=r"(w[i].z), "=r"(w[i].w)
                             : "l"(wq + (size_t)i * 32 * 8192), "l"(pol));
            const unsigned short* xp = (const unsigned short*)p.x + (tid >> 3);
#pragma unroll
            for (int i = 0; i < 14; i++) xr[i] = __ldg(xp + 32 * i);
        }
        if (tid < NBAR) {
            uint32_t cnt = 1;
            if (tid >= B_EMPTY && tid < B_PACE) {
                int t = tid - B_EMPTY;
                bool isk = t < NA || (t >= 2 * NA && t < 2 * NA + NB);
                cnt = isk ? 2 : 8;
            } else if ((tid >= B_PACE && tid <= B_QPART) || (tid >= B_VDONE && tid < B_OREADY)) {
                cnt = 8;
            }
            mbar_init(bars + 8 * tid, cnt);
            asm volatile("fence.mbarrier_init.release.cluster;" ::: "memory");
        }
        __syncthreads();
        {
            float a[8];
#pragma unroll
            for (int c = 0; c < 8; c++) a[c] = 0.f;
#pragma unroll
            for (int i = 0; i < 14; i++) {
                const float xv = __uint_as_float(xr[i] << 16);
                a[0] = fmaf(xv, bf_lo(w[i].x), a[0]); a[1] = fmaf(xv, bf_hi(w[i].x), a[1]);
                a[2] = fmaf(xv, bf_lo(w[i].y), a[2]); a[3] = fmaf(xv, bf_hi(w[i].y), a[3]);
                a[4] = fmaf(xv, bf_lo(w[i].z), a[4]); a[5] = fmaf(xv, bf_hi(w[i].z), a[5]);
                a[6] = fmaf(xv, bf_lo(w[i].w), a[6]); a[7] = fmaf(xv, bf_hi(w[i].w), a[7]);
                if (i + 1 == PACE0 || i + 1 == PACE1 || i + 1 == PACE2) {
                    const int k = (i + 1 == PACE0) ? 0 : (i + 1 == PACE1) ? 1 : 2;
                    asm volatile("" ::"f"(a[0]) : "memory");
                    if (lane == 0) mbar_arrive(bars + 8 * (B_PACE + k));
                }
            }
            const bool hi4 = lane & 16, hi3 = lane & 8;
            float b[4], c2[2];
#pragma unroll
            for (int c = 0; c < 4; c++) {
                const float send = hi4 ? a[c] : a[c + 4], keep = hi4 ? a[c + 4] : a[c];
                b[c] = keep + __shfl_xor_sync(0xffffffffu, send, 16);
            }
#pragma unroll
            for (int c = 0; c < 2; c++) {
                const float send = hi3 ? b[c] : b[c + 2], keep = hi3 ? b[c + 2] : b[c];
                c2[c] = keep + __shfl_xor_sync(0xffffffffu, send, 8);
            }
            const int col = 8 * (lane & 7) + (hi4 ? 4 : 0) + (hi3 ? 2 : 0);
            *(float2*)(smem + OFF_QR + (warp * 64 + col) * 4) = make_float2(c2[0], c2[1]);
            __syncwarp();
            if (lane == 0) mbar_arrive(bars + 8 * B_QPART);
        }
        if (tid == 0) STAMP(1);

        const int g = lane >> 2, t = lane & 3;
        const bool valid = t == (g & 3);
        uint32_t lm[2];
        {
            const int mi = lane >> 3, r = lane & 7;
#pragma unroll
            for (int b = 0; b < 2; b++) lm[b] = (8 * (mi >> 1) + r) * 512 + 16 * ((2 * b + (mi & 1)) ^ (r >> 1));
        }
        mbar_wait(bars + 8 * B_QREADY);
        if (tid == 0) STAMP(2);
        const uint32_t tag0 = *(volatile uint32_t*)(smem + OFF_TAG);

        int tile0 = 0;
#pragma unroll 1
        for (int br = 0; br < 2; br++) {
            const int nt = br ? NB : NA;
            uint32_t qa[32];
            {
                const uint32_t* qs = (const uint32_t*)(smem + OFF_Q) + br * 256 + (g >> 2) * 128 + t;
#pragma unroll
                for (int u = 0; u < 32; u++) qa[u] = qs[4 * (u ^ (g & 3))];
            }
            float mx = -INFINITY;
#pragma unroll 1
            for (int kt = warp >> 1; kt < nt; kt += 4) {
                const int T = tile0 + kt;
                mbar_wait(bars + 8 * (B_FULL + T));
                const uint32_t base = sb + (T % NS) * TILE + (warp & 1) * 8192;
                float c[4][4];
#pragma unroll
                for (int i = 0; i < 4; i++) c[i][0] = c[i][1] = c[i][2] = c[i][3] = 0.f;
#pragma unroll
                for (int a = 0; a < 8; a++) {
#pragma unroll
                    for (int b = 0; b < 2; b++) {
                        uint32_t r[4];
                        ldsm4(r, base + lm[b] + 64 * a);
                        const int u = 4 * a + 2 * b;
                        mma16816(c[b], qa[u], 0u, qa[u + 1], 0u, r[0], r[1]);
                        mma16816(c[2 + b], qa[u], 0u, qa[u + 1], 0u, r[2], r[3]);
                    }
                }
                __syncwarp();
                if (lane == 0) mbar_arrive(bars + 8 * (B_EMPTY + T));
                if (valid) {
                    float4 s;
                    s.x = round_bf(c[0][0] + c[1][0]); s.y = round_bf(c[0][1] + c[1][1]);
                    s.z = round_bf(c[2][0] + c[3][0]); s.w = round_bf(c[2][1] + c[3][1]);
                    *(float4*)(smem + OFF_S + ((2 * kt + (warp & 1)) * 8 + g) * 16) = s;
                    mx = fmaxf(fmaxf(mx, fmaxf(s.x, s.y)), fmaxf(s.z, s.w));
                }
            }
            mx = fmaxf(mx, __shfl_xor_sync(0xffffffffu, mx, 5));
            mx = fmaxf(mx, __shfl_xor_sync(0xffffffffu, mx, 10));
            float* mred = (float*)(smem + OFF_M) + br * 16;
            float* lred = (float*)(smem + OFF_L) + br * 16;
            if ((lane & 15) == 0) mred[(lane >> 4) * 8 + warp] = mx;
            asm volatile("bar.sync 1, 256;" ::: "memory");
            if (tid == 0) STAMP(3 + 3 * br);
            {
                const int hh = (tid >> 2) & 1;
                const float4 m0 = *(const float4*)(mred + hh * 8), m1 = *(const float4*)(mred + hh * 8 + 4);
                const float M = fmaxf(fmaxf(fmaxf(m0.x, m0.y), fmaxf(m0.z, m0.w)), fmaxf(fmaxf(m1.x, m1.y), fmaxf(m1.z, m1.w)));
                float l = 0.f;
                if (tid < nt * 16) {
                    const float4 s = *(const float4*)(smem + OFF_S + tid * 16);
                    const uint32_t p0 = pack_bf2(ex2((s.x - M) * SCALE_LOG2E), ex2((s.y - M) * SCALE_LOG2E));
                    const uint32_t p1 = pack_bf2(ex2((s.z - M) * SCALE_LOG2E), ex2((s.w - M) * SCALE_LOG2E));
                    const int unit = tid >> 3;
                    *(uint2*)(smem + OFF_P + ((unit >> 1) * 8 + (tid & 7)) * 16 + (unit & 1) * 8) = make_uint2(p0, p1);
                    l = (bf_lo(p0) + bf_hi(p0)) + (bf_lo(p1) + bf_hi(p1));
                }
                l += __shfl_xor_sync(0xffffffffu, l, 1);
                l += __shfl_xor_sync(0xffffffffu, l, 2);
                l += __shfl_xor_sync(0xffffffffu, l, 8);
                l += __shfl_xor_sync(0xffffffffu, l, 16);
                if ((lane & ~4) == 0) lred[(lane >> 2) * 8 + warp] = l;
            }
            asm volatile("bar.sync 1, 256;" ::: "memory");
            if (tid == 0) mbar_arrive(bars + 8 * (B_ML + br));
            tile0 += nt;
            float o[2][4];
#pragma unroll
            for (int i = 0; i < 2; i++) o[i][0] = o[i][1] = o[i][2] = o[i][3] = 0.f;
#pragma unroll 1
            for (int vt = 0; vt < nt; vt++) {
                const int T = tile0 + vt;
                uint4 pb = *(const uint4*)(smem + OFF_P + (vt * 8 + g) * 16);
                if (!valid) pb = make_uint4(0u, 0u, 0u, 0u);
                if (vt == nt - 1 && br) mbar_wait(bars + 8 * B_MLSEEN);
                mbar_wait(bars + 8 * (B_FULL + T));
                const uint32_t base = sb + (T % NS) * TILE + warp * 64;
                uint32_t r[4][4];
                ldsm4t(r[0], base + lm[0]);
                ldsm4t(r[1], base + lm[1]);
                ldsm4t(r[2], base + lm[0] + 8192);
                ldsm4t(r[3], base + lm[1] + 8192);
                mma16816(o[0], r[0][0], r[0][1], r[0][2], r[0][3], pb.x, pb.y);
                mma16816(o[1], r[1][0], r[1][1], r[1][2], r[1][3], pb.x, pb.y);
                mma16816(o[0], r[2][0], r[2][1], r[2][2], r[2][3], pb.z, pb.w);
                mma16816(o[1], r[3][0], r[3][1], r[3][2], r[3][3], pb.z, pb.w);
                __syncwarp();
                if (lane == 0) mbar_arrive(bars + 8 * (B_EMPTY + T));
            }
            tile0 += nt;
            if (tid == 0) STAMP(4 + 3 * br);
            {
                const float P0 = o[0][0] + o[0][3], P1 = o[0][2] + o[0][1];
                const float P2 = o[1][0] + o[1][3], P3 = o[1][2] + o[1][1];
                const float o0 = P0 + __shfl_xor_sync(0xffffffffu, P2, 1);
                const float o1 = P1 + __shfl_xor_sync(0xffffffffu, P3, 1);
                put2(&g_o[head][(t >> 1) * 8 + warp][j][(t & 1) * 8 + g], __float_as_uint(o0), __float_as_uint(o1), tag0 + br);
            }
            if (lane == 0) mbar_arrive(bars + 8 * (B_VDONE + br));
        }
        if (tid < DM / 2) {
            float y0 = 0.f, y1 = 0.f;
#pragma unroll 1
            for (int x = 0; x < 4; x++) {
                const int T = NKV + x;
                if (!(x & 1)) mbar_wait(bars + 8 * (B_OREADY + (x >> 1)));
                float ov[16];
#pragma unroll
                for (int i = 0; i < 4; i++) {
                    const float4 f = *(const float4*)(smem + OFF_O + (x * 16 + 4 * i) * 4);
                    ov[4 * i] = f.x; ov[4 * i + 1] = f.y; ov[4 * i + 2] = f.z; ov[4 * i + 3] = f.w;
                }
                mbar_wait(bars + 8 * (B_FULL + T));
                const uint32_t* wp = (const uint32_t*)(smem + (T % NS) * TILE) + tid;
                float z0 = 0.f, z1 = 0.f;
#pragma unroll
                for (int r = 0; r < 16; r += 2) {
                    const uint32_t w0 = wp[r * (DM / 2)], w1 = wp[(r + 1) * (DM / 2)];
                    y0 = fmaf(ov[r], bf_lo(w0), y0);     y1 = fmaf(ov[r], bf_hi(w0), y1);
                    z0 = fmaf(ov[r + 1], bf_lo(w1), z0); z1 = fmaf(ov[r + 1], bf_hi(w1), z1);
                }
                y0 += z0; y1 += z1;
                if (tid == 0) STAMP(9 + x);
            }
            put2(&g_y[tid >> 1][cta][tid & 1], __float_as_uint(y0), __float_as_uint(y1), tag0);
        }
    } else if (warp == 8) {
        __syncthreads();
        if (lane == 0) {
            uint64_t pol;
            asm volatile("createpolicy.fractional.L2::evict_first.b64 %0, 1.0;" : "=l"(pol));
            const size_t hoff = (size_t)head * SK * 512 + (size_t)j * TILE;
            int landed = 0;
#pragma unroll 1
            for (int i = 0; i < NT; i++) {
                const char* src;
                uint32_t bytes = TILE;
                int dep = i - WIN;
                if (i < 2 * NA) {
                    src = (i < NA ? p.k[0] : p.v[0]) + hoff + (size_t)(SK - WA) * 512 + (size_t)(i & (NA - 1)) * 16 * TILE;
                } else if (i < NKV) {
                    src = (i < 2 * NA + NB ? p.k[1] : p.v[1]) + hoff + (size_t)((i - 2 * NA) & (NB - 1)) * 16 * TILE;
                } else {
                    const int x = i - NKV;
                    src = p.wo[x >> 1] + (size_t)(cta * 2 + (x & 1)) * WOT;
                    bytes = WOT;
                    dep = NKV - WO_LEAD + x * WO_STEP;
                }
                if (i < 3) mbar_wait(bars + 8 * (B_PACE + i));
                for (; landed <= dep; landed++) mbar_wait(bars + 8 * (B_FULL + landed));
                if (i >= NS) mbar_wait(bars + 8 * (B_EMPTY + i - NS));
                mbar_expect_tx(bars + 8 * (B_FULL + i), bytes);
                bulk_load(sb + (i % NS) * TILE, src, bytes, bars + 8 * (B_FULL + i), pol);
                if (i == 0) STAMP(13);
                if (i == NKV) STAMP(14);
            }
        }
    } else {
        uint32_t ep;
        asm volatile("ld.relaxed.gpu.global.u32 %0, [%1];" : "=r"(ep) : "l"(&g_epoch) : "memory");
        uint32_t xg[7], gg[7];
#pragma unroll
        for (int i = 0; i < 7; i++) {
            xg[i] = __ldg((const uint32_t*)p.x + lane + 32 * i);
            gg[i] = __ldg((const uint32_t*)p.gw + lane + 32 * i);
        }
        __syncthreads();
        const uint32_t tag0 = 2 * ep + 2;
        if (lane == 0) *(volatile uint32_t*)(smem + OFF_TAG) = tag0;
        float gate;
        {
            float z = 0.f;
#pragma unroll
            for (int i = 0; i < 7; i++)
                z += round_bf(bf_lo(xg[i]) * bf_lo(gg[i])) + round_bf(bf_hi(xg[i]) * bf_hi(gg[i]));
#pragma unroll
            for (int s = 16; s; s >>= 1) z += __shfl_xor_sync(0xffffffffu, z, s);
            z = round_bf(z);
            gate = round_bf(1.f / (1.f + __expf(-z)));
        }
        uint4 v[8];
        mbar_wait(bars + 8 * B_QPART);
        {
            float q0 = 0.f, q1 = 0.f;
#pragma unroll
            for (int w8 = 0; w8 < 8; w8++) {
                const float2 f = *(const float2*)(smem + OFF_QR + (w8 * 64 + 2 * lane) * 4);
                q0 += f.x; q1 += f.y;
            }
            put1((char*)&g_q[head][j * 16] + lane * 8, pack_bf2(q0, q1), tag0);
            gather8(v, (const char*)&g_q[head][lane], tag0);
#pragma unroll
            for (int k = 0; k < 8; k++) *(uint2*)(smem + OFF_Q + (k * 32 + lane) * 8) = make_uint2(v[k].x, v[k].z);
            __syncwarp();
            if (lane == 0) mbar_arrive(bars + 8 * B_QREADY);
        }
#pragma unroll 1
        for (int br = 0; br < 2; br++) {
            const uint32_t tag = tag0 + br;
            mbar_wait(bars + 8 * (B_ML + br));
            __threadfence();
            if (lane < 2) {
                const float* mred = (const float*)(smem + OFF_M) + br * 16 + lane * 8;
                const float* lred = (const float*)(smem + OFF_L) + br * 16 + lane * 8;
                float m = mred[0], l = lred[0];
#pragma unroll
                for (int i = 1; i < 8; i++) { m = fmaxf(m, mred[i]); l += lred[i]; }
                put2(&g_ml[head][br][j][lane], __float_as_uint(m), __float_as_uint(l), tag);
            }
            float wgt;
            {
                uint4 ml;
                uint32_t n = 0;
                while (true) {
                    ml = get2(&g_ml[head][br][lane & 15][j >> 3]);
                    if (__all_sync(0xffffffffu, ml.y == tag && ml.w == tag)) break;
                    if (++n > SPIN_LIMIT) __trap();
                    __nanosleep(100);
                }
                const float m = __uint_as_float(ml.x);
                float M = m;
#pragma unroll
                for (int s = 8; s; s >>= 1) M = fmaxf(M, __shfl_xor_sync(0xffffffffu, M, s));
                const float e = ex2((m - M) * SCALE_LOG2E);
                float L = e * __uint_as_float(ml.z);
#pragma unroll
                for (int s = 8; s; s >>= 1) L += __shfl_xor_sync(0xffffffffu, L, s);
                wgt = e / L;
            }
            if (br) {
                __threadfence();
                if (lane == 0) mbar_arrive(bars + 8 * B_MLSEEN);
            }
            float wk[8];
#pragma unroll
            for (int k = 0; k < 8; k++) wk[k] = __shfl_sync(0xffffffffu, wgt, 2 * k + (lane >> 4));
            const float gb = br ? round_bf(1.f - gate) : gate;
            mbar_wait(bars + 8 * (B_VDONE + br));
            gather8(v, (const char*)&g_o[head][j][0][lane], tag);
            float o0 = 0.f, o1 = 0.f;
#pragma unroll
            for (int k = 0; k < 8; k++) {
                o0 = fmaf(wk[k], __uint_as_float(v[k].x), o0);
                o1 = fmaf(wk[k], __uint_as_float(v[k].z), o1);
            }
            o0 += __shfl_xor_sync(0xffffffffu, o0, 16);
            o1 += __shfl_xor_sync(0xffffffffu, o1, 16);
            {
                const int d = 16 * ((lane >> 3) & 1) + (lane & 7) + ((lane & 16) >> 1);
                ((float*)(smem + OFF_O))[br * 32 + d] = gb * round_bf((lane & 16) ? o1 : o0);
            }
            __syncwarp();
            if (lane == 0) mbar_arrive(bars + 8 * (B_OREADY + br));
            if (lane == 0) STAMP(5 + 3 * br);
        }
        if (cta < NRED) {
            gather8(v, (const char*)&g_y[cta][0][0] + lane * 16, tag0);
            float y0 = 0.f, y1 = 0.f;
#pragma unroll
            for (int k = 0; k < 8; k++) { y0 += __uint_as_float(v[k].x); y1 += __uint_as_float(v[k].z); }
#pragma unroll
            for (int s = 2; s < 32; s <<= 1) {
                y0 += __shfl_xor_sync(0xffffffffu, y0, s);
                y1 += __shfl_xor_sync(0xffffffffu, y1, s);
            }
            if (lane < 2) ((uint32_t*)p.out)[cta * 2 + lane] = pack_bf2(y0, y1);
            if (cta == 0 && lane == 0) g_epoch = ep + 1;
            if (lane == 0) STAMP(15);
        }
    }
}

}

extern "C" void kernel_launch(void* const* d_in, const int* in_sizes, int n_in, void* d_out, int out_size) {
    (void)in_sizes; (void)n_in; (void)out_size;
    Params p;
    p.x = (const __nv_bfloat16*)d_in[0];
    p.k[0] = (const char*)d_in[1];
    p.v[0] = (const char*)d_in[2];
    p.wq[0] = (const char*)d_in[3];
    p.wo[0] = (const char*)d_in[4];
    p.k[1] = (const char*)d_in[6];
    p.v[1] = (const char*)d_in[7];
    p.wq[1] = (const char*)d_in[8];
    p.wo[1] = (const char*)d_in[9];
    p.gw = (const __nv_bfloat16*)d_in[10];
    p.out = (__nv_bfloat16*)d_out;
    cudaFuncSetAttribute(gated_mix_decode_kernel, cudaFuncAttributeMaxDynamicSharedMemorySize, SMEM_BYTES);
    gated_mix_decode_kernel<<<NCTA, NTHREADS, SMEM_BYTES>>>(p);
}
```

```cpp
#include <cuda_runtime.h>
#include <cuda_bf16.h>
#include <stdint.h>

#define NS 11
#define WIN 5
#define WO_LEAD 5
#define WO_STEP 1
#define PACE0 2400
#define PACE_STEP 1200
#define WO_AFTER_PUB 0
#define YINIT 1
#define QINIT 1
#define YWAIT 1
#define YATOM 1
#define YSPLIT 0
#define YWARM 1
#define OINIT 1
#define YSTRIDE 256
#define RATE 648
#define RATE0 1500
#define RATE_WO 4
#define STAG 640
#define WMIN 1
#define LATE_A 1

namespace {

constexpr int DM = 448;
constexpr int SK = 8192;
constexpr int WA = 2048;
constexpr int NCTA = 128;
constexpr int TILE = 16384;
constexpr int NA = 4, NB = 16;
constexpr int NKV = 2 * (NA + NB);
constexpr int NT = NKV + 4;
constexpr int WOT = 16 * DM * 2;
constexpr int NTHREADS = 320;
constexpr int NRED = DM / 8;
constexpr uint32_t SPIN_LIMIT = 1u << 22;

constexpr int OFF_Q    = NS * TILE;
constexpr int OFF_S    = OFF_Q + 2048;
constexpr int OFF_P    = OFF_S + 4096;
constexpr int OFF_QR   = OFF_P + 2048;
constexpr int OFF_M    = OFF_QR + 2048;
constexpr int OFF_L    = OFF_M + 128;
constexpr int OFF_O    = OFF_L + 128;
constexpr int OFF_TAG  = OFF_O + 128;
constexpr int OFF_BAR  = OFF_TAG + 16;
constexpr int B_FULL = 0, B_EMPTY = NS, B_YDONE = 2 * NS, B_VDONE = B_YDONE + 1  , B_QREADY = B_VDONE + 2  ,
              B_ML = B_QREADY + 2  , B_OREADY = B_ML + 2  , NBAR = B_OREADY + 2;
static_assert(NS >= WIN + 4, "a K warp must never wait on a slot whose previous tile has not landed");
constexpr int SMEM_BYTES = OFF_BAR + NBAR * 8;

struct Params {
    const char* wq[2];
    const __nv_bfloat16 *x, *gw;
    const char *k[2], *v[2], *wo[2];
    __nv_bfloat16* out;
};

constexpr uint32_t TAGM = 15u;
__device__ unsigned int g_epoch;
__device__ uint4 g_q[8][256];
__device__ uint4 g_ml[2][8][16][2];
__device__ uint4 g_o[2][8][16][16][8];
__device__ uint4 g_y[NRED][NCTA][2];
__device__ float4 g_acc[NRED * 4 * YSTRIDE / 16];
#define STAMP(i)
#define STAMP2(i)
#define TREAD(v)
#define TPUT(i, v)
#define TDECL(v)

__device__ __forceinline__ void mbar_init(uint32_t bar, uint32_t cnt) {
    asm volatile("mbarrier.init.shared::cta.b64 [%0], %1;" ::"r"(bar), "r"(cnt) : "memory");
}
__device__ __forceinline__ void mbar_arrive(uint32_t bar) {
    asm volatile("mbarrier.arrive.shared::cta.b64 _, [%0];" ::"r"(bar) : "memory");
}
__device__ __forceinline__ void mbar_arrive_n(uint32_t bar, uint32_t n) {
    asm volatile("mbarrier.arrive.shared::cta.b64 _, [%0], %1;" ::"r"(bar), "r"(n) : "memory");
}
__device__ __forceinline__ void mbar_expect_tx(uint32_t bar, uint32_t bytes) {
    asm volatile("mbarrier.arrive.expect_tx.shared::cta.b64 _, [%0], %1;" ::"r"(bar), "r"(bytes) : "memory");
}
__device__ __forceinline__ void mbar_wait(uint32_t bar, uint32_t parity = 0) {
    uint32_t n = 0;
    while (true) {
        uint32_t ok;
        asm volatile("{\n.reg .pred p;\nmbarrier.try_wait.parity.shared::cta.b64 p, [%1], %2;\nselp.u32 %0, 1, 0, p;\n}\n"
                     : "=r"(ok) : "r"(bar), "r"(parity) : "memory");
        if (ok) break;
        if (++n > SPIN_LIMIT) __trap();
    }
}
__device__ __forceinline__ void bulk_load(uint32_t dst, const void* src, uint32_t bytes, uint32_t bar, uint64_t pol) {
    asm volatile("cp.async.bulk.shared::cluster.global.mbarrier::complete_tx::bytes.L2::cache_hint [%0], [%1], %2, [%3], %4;"
                 ::"r"(dst), "l"(src), "r"(bytes), "r"(bar), "l"(pol) : "memory");
}
__device__ __forceinline__ void ldsm4(uint32_t (&r)[4], uint32_t a) {
    asm volatile("ldmatrix.sync.aligned.m8n8.x4.shared.b16 {%0,%1,%2,%3}, [%4];"
                 : "=r"(r[0]), "=r"(r[1]), "=r"(r[2]), "=r"(r[3]) : "r"(a) : "memory");
}
__device__ __forceinline__ void ldsm4t(uint32_t (&r)[4], uint32_t a) {
    asm volatile("ldmatrix.sync.aligned.m8n8.x4.trans.shared.b16 {%0,%1,%2,%3}, [%4];"
                 : "=r"(r[0]), "=r"(r[1]), "=r"(r[2]), "=r"(r[3]) : "r"(a) : "memory");
}
__device__ __forceinline__ void mma16816(float (&c)[4], uint32_t a0, uint32_t a1, uint32_t a2, uint32_t a3,
                                         uint32_t b0, uint32_t b1) {
    asm volatile("mma.sync.aligned.m16n8k16.row.col.f32.bf16.bf16.f32 {%0,%1,%2,%3}, {%4,%5,%6,%7}, {%8,%9}, {%0,%1,%2,%3};"
                 : "+f"(c[0]), "+f"(c[1]), "+f"(c[2]), "+f"(c[3])
                 : "r"(a0), "r"(a1), "r"(a2), "r"(a3), "r"(b0), "r"(b1));
}
__device__ __forceinline__ float bf_lo(uint32_t v) { return __uint_as_float(v << 16); }
__device__ __forceinline__ float bf_hi(uint32_t v) { return __uint_as_float(v & 0xffff0000u); }
__device__ __forceinline__ uint32_t pack_bf2(float lo, float hi) {
    uint32_t r;
    asm("cvt.rn.bf16x2.f32 %0, %1, %2;" : "=r"(r) : "f"(hi), "f"(lo));
    return r;
}
__device__ __forceinline__ float round_bf(float v) { return bf_lo(pack_bf2(v, 0.f)); }
__device__ __forceinline__ float ex2(float v) {
    float r;
    asm("ex2.approx.ftz.f32 %0, %1;" : "=f"(r) : "f"(v));
    return r;
}
__device__ __forceinline__ uint32_t tagged(float v, uint32_t tag) { return (__float_as_uint(v) & ~TAGM) | tag; }
__device__ __forceinline__ float untag(uint32_t v) { return __uint_as_float(v & ~TAGM); }
__device__ __forceinline__ void put2(void* p, uint32_t a, uint32_t b) {
    asm volatile("st.relaxed.gpu.global.v2.b32 [%0], {%1, %2};" ::"l"(p), "r"(a), "r"(b) : "memory");
}
template <int N>
__device__ __forceinline__ void gather(uint4 (&v)[8], const void* p, uint32_t tag) {
    uint32_t need[N];
#pragma unroll
    for (int k = 0; k < N; k++) need[k] = 1;
    uint32_t n = 0;
    while (true) {
#pragma unroll
        for (int k = 0; k < N; k++)
            asm volatile("{\n.reg .pred p;\nsetp.ne.u32 p, %5, 0;\n@p ld.relaxed.gpu.global.v4.b32 {%0, %1, %2, %3}, [%4];\n}\n"
                         : "+r"(v[k].x), "+r"(v[k].y), "+r"(v[k].z), "+r"(v[k].w)
                         : "l"((const char*)p + 512 * k), "r"(need[k]) : "memory");
        uint32_t any = 0;
#pragma unroll
        for (int k = 0; k < N; k++) {
            need[k] = ((v[k].x ^ tag) | (v[k].y ^ tag) | (v[k].z ^ tag) | (v[k].w ^ tag)) & TAGM;
            any |= need[k];
        }
        if (__all_sync(0xffffffffu, any == 0)) break;
        if (++n > SPIN_LIMIT) __trap();
    }
}
__device__ __forceinline__ float fold4(const float (&a)[4], int lane, int s1, int s2) {
    const bool h1 = lane & s1, h2 = lane & s2;
    const float b0 = (h1 ? a[2] : a[0]) + __shfl_xor_sync(0xffffffffu, h1 ? a[0] : a[2], s1);
    const float b1 = (h1 ? a[3] : a[1]) + __shfl_xor_sync(0xffffffffu, h1 ? a[1] : a[3], s1);
    return (h2 ? b1 : b0) + __shfl_xor_sync(0xffffffffu, h2 ? b0 : b1, s2);
}

constexpr float SCALE_LOG2E = 0.0625f * 1.4426950408889634f;

__global__ void __launch_bounds__(NTHREADS, 1) gated_mix_decode_kernel(const __grid_constant__ Params p) {
    extern __shared__ __align__(1024) char smem[];
    const uint32_t sb = (uint32_t)__cvta_generic_to_shared(smem);
    const uint32_t bars = sb + OFF_BAR;
    TDECL(t_entry);
    TREAD(t_entry);
    uint32_t ns0;
    asm volatile("mov.u32 %0, %globaltimer_lo;" : "=r"(ns0));
    const int tid = threadIdx.x, lane = tid & 31;
    const int warp = __shfl_sync(0xffffffffu, tid >> 5, 0);
    const int cta = blockIdx.x, head = cta >> 4, j = cta & 15;

    if (warp == 9) {
        uint32_t ep;
        asm volatile("ld.relaxed.gpu.global.u32 %0, [%1];" : "=r"(ep) : "l"(&g_epoch) : "memory");
        void* const qdst = (char*)&g_q[head][j * 16] + lane * 8;
        if (QINIT) put2(qdst, 0u, 0u);
        uint32_t xg[7], gg[7];
#pragma unroll
        for (int i = 0; i < 7; i++) {
            xg[i] = __ldg((const uint32_t*)p.x + lane + 32 * i);
            gg[i] = __ldg((const uint32_t*)p.gw + lane + 32 * i);
        }
        const uint32_t tag = ep + 1;
        {
            float z = 0.f;
#pragma unroll
            for (int i = 0; i < 7; i++)
                z += round_bf(bf_lo(xg[i]) * bf_lo(gg[i])) + round_bf(bf_hi(xg[i]) * bf_hi(gg[i]));
#pragma unroll
            for (int s = 16; s; s >>= 1) z += __shfl_xor_sync(0xffffffffu, z, s);
            z = round_bf(z);
            const float gate = round_bf(1.f / (1.f + __expf(-z)));
            if (lane == 0)
                *(uint4*)(smem + OFF_TAG) = make_uint4(tag, __float_as_uint(gate), __float_as_uint(round_bf(1.f - gate)), 0u);
        }
        asm volatile("bar.sync 0, 320;" ::: "memory");
        uint4 v[8] = {};
        {
            float q0 = 0.f, q1 = 0.f;
#pragma unroll
            for (int w8 = 0; w8 < 8; w8++) {
                const float2 f = *(const float2*)(smem + OFF_QR + (w8 * 64 + 2 * lane) * 4);
                q0 += f.x; q1 += f.y;
            }
            const uint32_t q2 = pack_bf2(q0, q1);
            put2(qdst, (q2 << 16) | tag, (q2 & 0xffff0000u) | tag);
        }
#pragma unroll 1
        for (int br = 0; br < 2; br++) {
            gather<4>(v, &g_q[head][br * 128 + lane], tag);
#pragma unroll
            for (int k = 0; k < 4; k++)
                *(uint2*)(smem + OFF_Q + (br * 128 + k * 32 + lane) * 8) =
                    make_uint2(__byte_perm(v[k].x, v[k].y, 0x7632), __byte_perm(v[k].z, v[k].w, 0x7632));
            __syncwarp();
            if (lane == 0) mbar_arrive(bars + 8 * (B_QREADY + br));
        }
#pragma unroll 1
        for (int br = 0; br < 2; br++) {
            mbar_wait(bars + 8 * (B_ML + br));
            if (lane < 4) {
                const float* mred = (const float*)(smem + OFF_M) + br * 16 + (lane & 1) * 8;
                const float* lred = (const float*)(smem + OFF_L) + br * 16 + (lane & 1) * 8;
                float m = mred[0], l = lred[0];
#pragma unroll
                for (int i = 1; i < 8; i++) { m = fmaxf(m, mred[i]); l += lred[i]; }
                put2((char*)&g_ml[br][head][j][0] + lane * 8, tagged(m, tag), tagged(l, tag));
            }
        }
#pragma unroll 1
        for (int br = 0; br < 2; br++) {
            float wk[4];
            {
                gather<1>(v, &g_ml[br][head][lane & 15][0], tag);
                const float m = untag((j & 8) ? v[0].z : v[0].x);
                float M = m;
#pragma unroll
                for (int s = 8; s; s >>= 1) M = fmaxf(M, __shfl_xor_sync(0xffffffffu, M, s));
                const float e = ex2((m - M) * SCALE_LOG2E);
                float L = e * untag((j & 8) ? v[0].w : v[0].y);
#pragma unroll
                for (int s = 8; s; s >>= 1) L += __shfl_xor_sync(0xffffffffu, L, s);
                const float wgt = e / L;
#pragma unroll
                for (int k = 0; k < 4; k++) wk[k] = __shfl_sync(0xffffffffu, wgt, 4 * k + (lane >> 3));
            }
            mbar_wait(bars + 8 * (B_VDONE + br));
            gather<4>(v, &g_o[br][head][j][0][0] + lane, tag);
            float o[4] = {0.f, 0.f, 0.f, 0.f};
#pragma unroll
            for (int k = 0; k < 4; k++) {
                o[0] = fmaf(wk[k], untag(v[k].x), o[0]); o[1] = fmaf(wk[k], untag(v[k].y), o[1]);
                o[2] = fmaf(wk[k], untag(v[k].z), o[2]); o[3] = fmaf(wk[k], untag(v[k].w), o[3]);
            }
            const float od = fold4(o, lane, 8, 16);
            const int d = 4 * (lane & 4) + 2 * (lane & 3) + ((lane >> 3) & 1) + ((lane & 16) >> 1);
            ((unsigned short*)(smem + OFF_O))[br * 32 + d] = (unsigned short)pack_bf2(od, 0.f);
            __syncwarp();
            if (lane == 0) mbar_arrive(bars + 8 * (B_OREADY + br));
            if (lane == 0) STAMP2(5 + 3 * br);
        }
        if (!YATOM && cta < NRED) {
            TDECL(ta); TDECL(tb);
            if (YWAIT) mbar_wait(bars + 8 * B_YDONE);
            TREAD(ta);
            gather<8>(v, &g_y[cta][0][0] + lane, tag);
            TREAD(tb);
            float y[4];
            y[0] = ((untag(v[0].x) + untag(v[1].x)) + (untag(v[2].x) + untag(v[3].x))) + ((untag(v[4].x) + untag(v[5].x)) + (untag(v[6].x) + untag(v[7].x)));
            y[1] = ((untag(v[0].y) + untag(v[1].y)) + (untag(v[2].y) + untag(v[3].y))) + ((untag(v[4].y) + untag(v[5].y)) + (untag(v[6].y) + untag(v[7].y)));
            y[2] = ((untag(v[0].z) + untag(v[1].z)) + (untag(v[2].z) + untag(v[3].z))) + ((untag(v[4].z) + untag(v[5].z)) + (untag(v[6].z) + untag(v[7].z)));
            y[3] = ((untag(v[0].w) + untag(v[1].w)) + (untag(v[2].w) + untag(v[3].w))) + ((untag(v[4].w) + untag(v[5].w)) + (untag(v[6].w) + untag(v[7].w)));
            float yy = fold4(y, lane, 2, 4);
            yy += __shfl_xor_sync(0xffffffffu, yy, 8);
            yy += __shfl_xor_sync(0xffffffffu, yy, 16);
            if (lane < 8)
                ((unsigned short*)p.out)[16 * (cta >> 1) + 4 * (cta & 1) + 2 * (lane & 1) + ((lane >> 1) & 1) + 2 * (lane & 4)] =
                    (unsigned short)pack_bf2(yy, 0.f);
            if (cta == 0 && lane == 0) g_epoch = (tag == TAGM) ? 0u : tag;
            if (lane == 0) STAMP(15);
            if (lane == 0) { TPUT(24, ta); TPUT(25, tb); }
        }
    } else if (warp == 8) {
        if (lane == 0) TPUT(0, t_entry);
        const uint32_t clk0 = clock();
        ns0 += RATE0 + STAG * ((cta * 37) & 127) / 128;
        if (lane == 0) {
#pragma unroll
            for (int i = 0; i < NBAR; i++) mbar_init(bars + 8 * i, (i >= B_EMPTY && i < B_QREADY) ? 8 : 1);
            asm volatile("fence.mbarrier_init.release.cluster;" ::: "memory");
        }
        __syncwarp();
        asm volatile("bar.arrive 0, 320;" ::: "memory");
        if (lane == 0) {
            uint64_t pol;
            asm volatile("createpolicy.fractional.L2::evict_first.b64 %0, 1.0;" : "=l"(pol));
            const size_t hoff = (size_t)head * SK * 512 + (size_t)j * TILE;
            int landed = 0;
#pragma unroll 1
            for (int i = 0; i < NT; i++) {
                const char* src;
                uint32_t bytes = TILE;
                int dep = i - WIN;
                if (i < 2 * NA) {
                    src = (i < NA ? p.k[0] : p.v[0]) + hoff + (size_t)(SK - WA) * 512 + (size_t)(i & (NA - 1)) * 16 * TILE;
                } else if (i < NKV) {
                    src = (i < 2 * NA + NB ? p.k[1] : p.v[1]) + hoff + (size_t)((i - 2 * NA) & (NB - 1)) * 16 * TILE;
                } else {
                    const int x = i - NKV;
                    src = p.wo[x >> 1] + (size_t)(cta * 2 + (x & 1)) * WOT;
                    bytes = WOT;
                    dep = NKV - WO_LEAD + x * WO_STEP;
                }
                const int slot = i % NS;
                if (!RATE && i < WIN) while ((uint32_t)(clock() - clk0) < (uint32_t)(PACE0 + i * PACE_STEP)) {}
                if (i >= NS) mbar_wait(bars + 8 * (B_EMPTY + slot), (i / NS - 1) & 1);
                for (; landed <= dep; landed++) mbar_wait(bars + 8 * (B_FULL + landed % NS), (landed / NS) & 1);
                if (RATE && i < NKV + RATE_WO) {
                    const int e = i - WMIN;
                    const uint32_t due = ns0 + (i <= NKV ? RATE * i : RATE * NKV + (i - NKV) * (RATE * 7 / 8));
                    while (true) {
                        uint32_t now, ok = 0;
                        asm volatile("mov.u32 %0, %globaltimer_lo;" : "=r"(now));
                        if ((int)(now - due) >= 0) break;
                        if (e >= 0) asm volatile("{\n.reg .pred p;\nmbarrier.test_wait.parity.shared::cta.b64 p, [%1], %2;\nselp.u32 %0, 1, 0, p;\n}\n"
                                     : "=r"(ok) : "r"(bars + 8 * (B_FULL + e % NS)), "r"((e / NS) & 1) : "memory");
                        if (ok) break;
                    }
                }
                if (WO_AFTER_PUB && i == NKV + WO_AFTER_PUB - 1) mbar_wait(bars + 8 * (B_VDONE + 1));
                mbar_expect_tx(bars + 8 * (B_FULL + slot), bytes);
                bulk_load(sb + slot * TILE, src, bytes, bars + 8 * (B_FULL + slot), pol);
                if (i == 0) STAMP2(13);
                if (i == NKV) STAMP2(14);
            }
        }
    } else {
        uint4 w[14];
        uint32_t xw;
        {
            uint64_t pol;
            asm volatile("createpolicy.fractional.L2::evict_first.b64 %0, 1.0;" : "=l"(pol));
            const char* wq = ((j & 8) ? p.wq[1] : p.wq[0]) + (uint32_t)((tid >> 3) * (14 * 8192) + (head * 512 + (j & 7) * 64) * 2 + (tid & 7) * 16);
            asm volatile("ld.global.nc.u32 %0, [%1];" : "=r"(xw) : "l"((const uint32_t*)p.x + (uint32_t)(warp * 28 + min(lane, 27))));
#pragma unroll
            for (int i = 0; i < 14; i++)
                asm volatile("ld.global.nc.L1::no_allocate.L2::cache_hint.v4.u32 {%0,%1,%2,%3}, [%4], %5;"
                             : "=r"(w[i].x), "=r"(w[i].y), "=r"(w[i].z), "=r"(w[i].w)
                             : "l"(wq + (size_t)i * 8192), "l"(pol));
        }
        const int g = lane >> 2, t = lane & 3;
        void* const ydst = (char*)&g_y[warp * 8 + 2 * t + (g >> 2)][cta][0] + (g & 3) * 8;
        char* const odst = (char*)&g_o[0][head][(t >> 1) * 8 + warp][j][0] + ((t & 1) * 8 + g) * 8;
        if (YINIT) {
            if (!YATOM && warp < 7) put2(ydst, 0u, 0u);
            if (OINIT) put2(odst + sizeof(g_o[0]), 0u, 0u);
        }
        {
            float a[8];
#pragma unroll
            for (int c = 0; c < 8; c++) a[c] = 0.f;
#pragma unroll
            for (int i = 0; i < 14; i++) {
                const uint32_t x2 = __shfl_sync(0xffffffffu, xw, 7 * (lane >> 3) + (i >> 1));
                const float xv = (i & 1) ? bf_hi(x2) : bf_lo(x2);
                a[0] = fmaf(xv, bf_lo(w[i].x), a[0]); a[1] = fmaf(xv, bf_hi(w[i].x), a[1]);
                a[2] = fmaf(xv, bf_lo(w[i].y), a[2]); a[3] = fmaf(xv, bf_hi(w[i].y), a[3]);
                a[4] = fmaf(xv, bf_lo(w[i].z), a[4]); a[5] = fmaf(xv, bf_hi(w[i].z), a[5]);
                a[6] = fmaf(xv, bf_lo(w[i].w), a[6]); a[7] = fmaf(xv, bf_hi(w[i].w), a[7]);
            }
            const bool hi4 = lane & 16, hi3 = lane & 8;
            float b[4], c2[2];
#pragma unroll
            for (int c = 0; c < 4; c++) {
                const float send = hi4 ? a[c] : a[c + 4], keep = hi4 ? a[c + 4] : a[c];
                b[c] = keep + __shfl_xor_sync(0xffffffffu, send, 16);
            }
#pragma unroll
            for (int c = 0; c < 2; c++) {
                const float send = hi3 ? b[c] : b[c + 2], keep = hi3 ? b[c + 2] : b[c];
                c2[c] = keep + __shfl_xor_sync(0xffffffffu, send, 8);
            }
            const int col = 8 * (lane & 7) + (hi4 ? 4 : 0) + (hi3 ? 2 : 0);
            *(float2*)(smem + OFF_QR + (warp * 64 + col) * 4) = make_float2(c2[0], c2[1]);
            asm volatile("bar.sync 0, 320;" ::: "memory");
        }
        if (tid == 0) STAMP2(1);

        const bool valid = t == (g & 3);
        uint32_t lm[2];
        {
            const int mi = lane >> 3, r = lane & 7;
#pragma unroll
            for (int b = 0; b < 2; b++) lm[b] = (8 * (mi >> 1) + r) * 512 + 16 * ((2 * b + (mi & 1)) ^ (r >> 1));
        }
        const uint32_t tag = *(const uint32_t*)(smem + OFF_TAG);

        int tile0 = 0;
#pragma unroll 1
        for (int br = 0; br < 2; br++) {
            const int nt = br ? NB : NA;
            mbar_wait(bars + 8 * (B_QREADY + br));
            if (tid == 0 && br == 0) STAMP2(2);
            uint32_t qa[32];
            {
                const uint32_t* qs = (const uint32_t*)(smem + OFF_Q) + br * 256 + (g >> 2) * 128 + t;
#pragma unroll
                for (int u = 0; u < 32; u++) qa[u] = qs[4 * (u ^ (g & 3))];
            }
            float mx = -INFINITY;
#pragma unroll 1
            for (int kt = warp >> 1; kt < nt; kt += 4) {
                const int T = tile0 + kt;
                const int slot = T % NS;
                mbar_wait(bars + 8 * (B_FULL + slot), (T / NS) & 1);
                const uint32_t base = sb + slot * TILE + (warp & 1) * 8192;
                float c[4][4];
#pragma unroll
                for (int i = 0; i < 4; i++) c[i][0] = c[i][1] = c[i][2] = c[i][3] = 0.f;
#pragma unroll
                for (int a = 0; a < 8; a++) {
#pragma unroll
                    for (int b = 0; b < 2; b++) {
                        uint32_t r[4];
                        ldsm4(r, base + lm[b] + 64 * a);
                        const int u = 4 * a + 2 * b;
                        mma16816(c[b], qa[u], 0u, qa[u + 1], 0u, r[0], r[1]);
                        mma16816(c[2 + b], qa[u], 0u, qa[u + 1], 0u, r[2], r[3]);
                    }
                }
                __syncwarp();
                if (lane == 0) mbar_arrive_n(bars + 8 * (B_EMPTY + slot), 4);
                if (valid) {
                    float4 s;
                    s.x = round_bf(c[0][0] + c[1][0]); s.y = round_bf(c[0][1] + c[1][1]);
                    s.z = round_bf(c[2][0] + c[3][0]); s.w = round_bf(c[2][1] + c[3][1]);
                    *(float4*)(smem + OFF_S + ((2 * kt + (warp & 1)) * 8 + g) * 16) = s;
                    mx = fmaxf(fmaxf(mx, fmaxf(s.x, s.y)), fmaxf(s.z, s.w));
                }
            }
            mx = fmaxf(mx, __shfl_xor_sync(0xffffffffu, mx, 5));
            mx = fmaxf(mx, __shfl_xor_sync(0xffffffffu, mx, 10));
            float* mred = (float*)(smem + OFF_M) + br * 16;
            float* lred = (float*)(smem + OFF_L) + br * 16;
            if ((lane & 15) == 0) mred[(lane >> 4) * 8 + warp] = mx;
            asm volatile("bar.sync 1, 256;" ::: "memory");
            if (tid == 0) STAMP2(3 + 3 * br);
            {
                const int hh = (tid >> 2) & 1;
                const float4 m0 = *(const float4*)(mred + hh * 8), m1 = *(const float4*)(mred + hh * 8 + 4);
                const float M = fmaxf(fmaxf(fmaxf(m0.x, m0.y), fmaxf(m0.z, m0.w)), fmaxf(fmaxf(m1.x, m1.y), fmaxf(m1.z, m1.w)));
                float l = 0.f;
                if (tid < nt * 16) {
                    const float4 s = *(const float4*)(smem + OFF_S + tid * 16);
                    const uint32_t p0 = pack_bf2(ex2((s.x - M) * SCALE_LOG2E), ex2((s.y - M) * SCALE_LOG2E));
                    const uint32_t p1 = pack_bf2(ex2((s.z - M) * SCALE_LOG2E), ex2((s.w - M) * SCALE_LOG2E));
                    const int unit = tid >> 3;
                    *(uint2*)(smem + OFF_P + ((unit >> 1) * 8 + (tid & 7)) * 16 + (unit & 1) * 8) = make_uint2(p0, p1);
                    l = (bf_lo(p0) + bf_hi(p0)) + (bf_lo(p1) + bf_hi(p1));
                }
                l += __shfl_xor_sync(0xffffffffu, l, 1);
                l += __shfl_xor_sync(0xffffffffu, l, 2);
                l += __shfl_xor_sync(0xffffffffu, l, 8);
                l += __shfl_xor_sync(0xffffffffu, l, 16);
                if ((lane & ~4) == 0) lred[(lane >> 2) * 8 + warp] = l;
            }
            asm volatile("bar.sync 1, 256;" ::: "memory");
            if (tid == 0) mbar_arrive(bars + 8 * (B_ML + br));
            tile0 += nt;
            float o[2][4];
#pragma unroll
            for (int i = 0; i < 2; i++) o[i][0] = o[i][1] = o[i][2] = o[i][3] = 0.f;
#pragma unroll 1
            for (int vt = 0; vt < nt; vt++) {
                const int T = tile0 + vt;
                uint4 pb = *(const uint4*)(smem + OFF_P + (vt * 8 + g) * 16);
                if (!valid) pb = make_uint4(0u, 0u, 0u, 0u);
                const int slot = T % NS;
                mbar_wait(bars + 8 * (B_FULL + slot), (T / NS) & 1);
                const uint32_t base = sb + slot * TILE + warp * 64;
                uint32_t r[4][4];
                ldsm4t(r[0], base + lm[0]);
                ldsm4t(r[1], base + lm[1]);
                ldsm4t(r[2], base + lm[0] + 8192);
                ldsm4t(r[3], base + lm[1] + 8192);
                mma16816(o[0], r[0][0], r[0][1], r[0][2], r[0][3], pb.x, pb.y);
                mma16816(o[1], r[1][0], r[1][1], r[1][2], r[1][3], pb.x, pb.y);
                mma16816(o[0], r[2][0], r[2][1], r[2][2], r[2][3], pb.z, pb.w);
                mma16816(o[1], r[3][0], r[3][1], r[3][2], r[3][3], pb.z, pb.w);
                __syncwarp();
                if (lane == 0) mbar_arrive(bars + 8 * (B_EMPTY + slot));
            }
            tile0 += nt;
            if (tid == 0) STAMP2(4 + 3 * br);
            {
                const float P0 = o[0][0] + o[0][3], P1 = o[0][2] + o[0][1];
                const float P2 = o[1][0] + o[1][3], P3 = o[1][2] + o[1][1];
                const float o0 = P0 + __shfl_xor_sync(0xffffffffu, P2, 1);
                const float o1 = P1 + __shfl_xor_sync(0xffffffffu, P3, 1);
                put2(odst + br * sizeof(g_o[0]), tagged(o0, tag), tagged(o1, tag));
            }
            if (lane == 0) mbar_arrive(bars + 8 * (B_VDONE + br));
        }
        if (warp < 7) {
            uint32_t wm[4];
            {
                const int mi = lane >> 3, r = lane & 7;
#pragma unroll
                for (int i = 0; i < 4; i++)
                    wm[i] = sb + (8 * (mi >> 1) + r) * (DM * 2) + 16 * (8 * warp + ((2 * i + (mi & 1)) ^ r));
            }
            const uint32_t msk = (g >> 1) != t ? 0u : (g & 1) ? 0xffff0000u : 0x0000ffffu;
            char* ap = (char*)g_acc + (YSPLIT ? tid * YSTRIDE : (tid >> 1) * YSTRIDE + (tid & 1) * 16);
            float P[8];
            TDECL(ta); TDECL(tb); TDECL(tc); TDECL(td);
#pragma unroll
            for (int v = 0; v < 8; v++) P[v] = 0.f;
#pragma unroll
            for (int br = 0; br < 2; br++) {
                const float gb = *(const float*)(smem + OFF_TAG + 4 + 4 * br);
                mbar_wait(bars + 8 * (B_OREADY + br));
                if (br) TREAD(ta);
                uint32_t ob[4];
#pragma unroll
                for (int i = 0; i < 4; i++) ob[i] = ((const uint32_t*)(smem + OFF_O))[br * 16 + 4 * i + t] & msk;
                float c[4][4];
#pragma unroll
                for (int i = 0; i < 4; i++) c[i][0] = c[i][1] = c[i][2] = c[i][3] = 0.f;
#pragma unroll
                for (int x = 0; x < 2; x++) {
                    const int T = NKV + 2 * br + x;
                    mbar_wait(bars + 8 * (B_FULL + T % NS), (T / NS) & 1);
                    if (br && x == 0) TREAD(tb);
                    if (br && x == 1) TREAD(tc);
                    uint32_t r[4][4];
#pragma unroll
                    for (int i = 0; i < 4; i++) ldsm4t(r[i], wm[i] + (T % NS) * TILE);
#pragma unroll
                    for (int i = 0; i < 4; i++) mma16816(c[i], r[i][0], r[i][1], r[i][2], r[i][3], ob[2 * x], ob[2 * x + 1]);
                    if (tid == 32) STAMP2(9 + 2 * br + x);
                }
#pragma unroll
                for (int i = 0; i < 4; i++) {
                    P[2 * i] = fmaf(gb, c[i][0] + c[i][3], P[2 * i]);
                    P[2 * i + 1] = fmaf(gb, c[i][2] + c[i][1], P[2 * i + 1]);
                }
                if (YWARM && br == 0 && cta == 0) {
                    const float Q0 = P[0] + __shfl_xor_sync(0xffffffffu, P[2], 1);
                    const float Q1 = P[1] + __shfl_xor_sync(0xffffffffu, P[3], 1);
                    const float Q4 = P[4] + __shfl_xor_sync(0xffffffffu, P[6], 1);
                    const float Q5 = P[5] + __shfl_xor_sync(0xffffffffu, P[7], 1);
                    const float y0 = Q0 + __shfl_xor_sync(0xffffffffu, Q4, 2);
                    const float y1 = Q1 + __shfl_xor_sync(0xffffffffu, Q5, 2);
                    asm volatile("red.relaxed.gpu.global.add.v2.f32 [%0], {%1, %2};" ::"l"(ap), "f"(y0), "f"(y1) : "memory");
#pragma unroll
                    for (int v = 0; v < 8; v++) P[v] = 0.f;
                }
            }
            const float Q0 = P[0] + __shfl_xor_sync(0xffffffffu, P[2], 1);
            const float Q1 = P[1] + __shfl_xor_sync(0xffffffffu, P[3], 1);
            const float Q4 = P[4] + __shfl_xor_sync(0xffffffffu, P[6], 1);
            const float Q5 = P[5] + __shfl_xor_sync(0xffffffffu, P[7], 1);
            const float y0 = Q0 + __shfl_xor_sync(0xffffffffu, Q4, 2);
            const float y1 = Q1 + __shfl_xor_sync(0xffffffffu, Q5, 2);
            if (YATOM) {
                float a0, a1, a2;
                TREAD(td);
                asm volatile("{\n.reg .f32 d;\natom.relaxed.gpu.global.add.v4.f32 {%0, %1, %2, d}, [%3], {%4, %5, %6, %6};\n}\n"
                             : "=f"(a0), "=f"(a1), "=f"(a2) : "l"(ap), "f"(y0), "f"(y1), "f"(1.f) : "memory");
                if (a2 == (float)(NCTA - 1)) {
                    const uint32_t r = pack_bf2(a0 + y0, a1 + y1);
                    unsigned short* op = (unsigned short*)p.out + 64 * warp + 16 * t + g;
                    op[0] = (unsigned short)r;
                    op[8] = (unsigned short)(r >> 16);
                    *(float4*)ap = make_float4(0.f, 0.f, 0.f, 0.f);
                    if (tid == 0) g_epoch = (tag == TAGM) ? 0u : tag;
                }
                if (tid == 0) STAMP(15);
            } else {
                put2(ydst, tagged(y0, tag), tagged(y1, tag));
                TREAD(td);
            }
            if (tid == 0) { TPUT(20, ta); TPUT(21, tb); TPUT(22, tc); TPUT(23, td); }
        }
        if (YWAIT && lane == 0) mbar_arrive(bars + 8 * B_YDONE);
    }
}

}

extern "C" void kernel_launch(void* const* d_in, const int* in_sizes, int n_in, void* d_out, int out_size) {
    (void)in_sizes; (void)n_in; (void)out_size;
    Params p;
    p.x = (const __nv_bfloat16*)d_in[0];
    p.k[0] = (const char*)d_in[1];
    p.v[0] = (const char*)d_in[2];
    p.wq[0] = (const char*)d_in[3];
    p.wo[0] = (const char*)d_in[4];
    p.k[1] = (const char*)d_in[6];
    p.v[1] = (const char*)d_in[7];
    p.wq[1] = (const char*)d_in[8];
    p.wo[1] = (const char*)d_in[9];
    p.gw = (const __nv_bfloat16*)d_in[10];
    p.out = (__nv_bfloat16*)d_out;
    cudaFuncSetAttribute(gated_mix_decode_kernel, cudaFuncAttributeMaxDynamicSharedMemorySize, SMEM_BYTES);
    gated_mix_decode_kernel<<<NCTA, NTHREADS, SMEM_BYTES>>>(p);
}
```

```cpp
#include <cuda_runtime.h>
#include <cuda_bf16.h>
#include <stdint.h>
#include <stddef.h>

#define NS 10
#define WIN 5
#define WMIN 1
#define RATE 652
#define RATE0 1400
#define WORATE (RATE * 7 / 8)
#define STAG 5
#define QDELAY 500
#define OWAIT 40
#define ODELAY 200

namespace {

constexpr int DM = 448;
constexpr int SK = 8192;
constexpr int WA = 2048;
constexpr int NCTA = 128;
constexpr int TILE = 16384;
constexpr int NA = 4, NB = 16;
constexpr int NKV = 2 * (NA + NB);
constexpr int NT = NKV + 4;
constexpr int WOT = 16 * DM * 2;
constexpr int NTHREADS = 320;
constexpr uint32_t SPIN_LIMIT = 1u << 18;
constexpr uint64_t EVICT_FIRST = 0x12F0000000000000ull;

constexpr int OFF_W    = 0;
constexpr int OFF_RING = 4 * WOT;
constexpr int QS = 576;
constexpr int OFF_Q    = OFF_RING + NS * TILE;
constexpr int OFF_S    = OFF_Q + 4 * QS;
constexpr int OFF_P    = OFF_S + 4096;
constexpr int OFF_M    = OFF_P + 2048;
constexpr int OFF_L    = OFF_M + 128;
constexpr int OFF_O    = OFF_L + 128;
constexpr int OFF_TAG  = OFF_O + 128;
constexpr int OFF_BAR  = OFF_TAG + 16;
constexpr int B_FULL = 0, B_ML = NT  , B_OREADY = B_ML + 2  , NBAR1 = B_OREADY + 2,
              B_EMPTY = NBAR1, NBAR = 2 * NBAR1;
constexpr int SMEM_BYTES = OFF_BAR + NBAR * 8;

constexpr uint32_t TAGM = 15u;
struct Scratch {
    float4 acc[2048];
    uint4 o[2][8][16][16][8];
    uint4 q[8][256];
    uint4 ml[2][8][16][2];
    unsigned int epoch;
};
__device__ uint4 g_scratch[(sizeof(Scratch) + 32768) / 16];

struct Params {
    const char* wq[2];
    const char *x, *gw;
    Scratch* sc;
    unsigned short* out;
    const char* seg[6];
};

#define STAMP(i)

__device__ __forceinline__ void mbar_arrive(uint32_t bar) {
    asm volatile("mbarrier.arrive.shared::cta.b64 _, [%0];" ::"r"(bar) : "memory");
}
__device__ __forceinline__ void mbar_wait(uint32_t bar) {
    asm volatile("{\n.reg .pred p, q;\n.reg .u32 n;\nmov.u32 n, 0;\n"
                 "W:\nmbarrier.try_wait.parity.shared::cta.b64 p, [%0], 0;\nadd.u32 n, n, 1;\n"
                 "setp.lt.and.u32 q, n, %1, !p;\n@q bra W;\n}\n" ::"r"(bar), "n"(SPIN_LIMIT) : "memory");
}
__device__ __forceinline__ void ldsm4(uint32_t (&r)[4], uint32_t a) {
    asm volatile("ldmatrix.sync.aligned.m8n8.x4.shared.b16 {%0,%1,%2,%3}, [%4];"
                 : "=r"(r[0]), "=r"(r[1]), "=r"(r[2]), "=r"(r[3]) : "r"(a) : "memory");
}
__device__ __forceinline__ void ldsm4t(uint32_t (&r)[4], uint32_t a) {
    asm volatile("ldmatrix.sync.aligned.m8n8.x4.trans.shared.b16 {%0,%1,%2,%3}, [%4];"
                 : "=r"(r[0]), "=r"(r[1]), "=r"(r[2]), "=r"(r[3]) : "r"(a) : "memory");
}
__device__ __forceinline__ void mma16816(float (&c)[4], const uint32_t (&a)[4], uint32_t b0, uint32_t b1) {
    asm("mma.sync.aligned.m16n8k16.row.col.f32.bf16.bf16.f32 {%0,%1,%2,%3}, {%4,%5,%6,%7}, {%8,%9}, {%0,%1,%2,%3};"
        : "+f"(c[0]), "+f"(c[1]), "+f"(c[2]), "+f"(c[3])
        : "r"(a[0]), "r"(a[1]), "r"(a[2]), "r"(a[3]), "r"(b0), "r"(b1));
}
__device__ __forceinline__ float bf_lo(uint32_t v) { return __uint_as_float(v << 16); }
__device__ __forceinline__ float bf_hi(uint32_t v) { return __uint_as_float(v & 0xffff0000u); }
__device__ __forceinline__ uint32_t pack_bf2(float lo, float hi) {
    uint32_t r;
    asm("cvt.rn.bf16x2.f32 %0, %1, %2;" : "=r"(r) : "f"(hi), "f"(lo));
    return r;
}
__device__ __forceinline__ float round_bf(float v) { return __uint_as_float(pack_bf2(0.f, v)); }
__device__ __forceinline__ float ex2(float v) {
    float r;
    asm("ex2.approx.ftz.f32 %0, %1;" : "=f"(r) : "f"(v));
    return r;
}
__device__ __forceinline__ float rcp(float v) {
    float r;
    asm("rcp.approx.ftz.f32 %0, %1;" : "=f"(r) : "f"(v));
    return r;
}
__device__ __forceinline__ float shx(float v, int m) { return __shfl_xor_sync(0xffffffffu, v, m); }
__device__ __forceinline__ uint32_t tagged(float v, uint32_t tag) { return (__float_as_uint(v) & ~TAGM) | tag; }
__device__ __forceinline__ float untag(uint32_t v) { return __uint_as_float(v & ~TAGM); }
__device__ __forceinline__ void put2(void* p, uint32_t a, uint32_t b) {
    asm volatile("st.relaxed.gpu.global.v2.b32 [%0], {%1, %2};" ::"l"(p), "r"(a), "r"(b) : "memory");
}
template <int N>
__device__ __forceinline__ void gather(uint4 (&v)[N], const void* p, uint32_t tag) {
    uint32_t need[N];
#pragma unroll
    for (int k = 0; k < N; k++) need[k] = 1;
#pragma unroll 1
    for (uint32_t n = 0; n < SPIN_LIMIT; n++) {
#pragma unroll
        for (int k = 0; k < N; k++)
            asm volatile("{\n.reg .pred p;\nsetp.ne.u32 p, %5, 0;\n@p ld.relaxed.gpu.global.v4.b32 {%0, %1, %2, %3}, [%4];\n}\n"
                         : "+r"(v[k].x), "+r"(v[k].y), "+r"(v[k].z), "+r"(v[k].w)
                         : "l"((const char*)p + 512 * k), "r"(need[k]) : "memory");
        uint32_t any = 0;
#pragma unroll
        for (int k = 0; k < N; k++) {
            need[k] = ((v[k].x ^ tag) | (v[k].y ^ tag) | (v[k].z ^ tag) | (v[k].w ^ tag)) & TAGM;
            any |= need[k];
        }
        if (__all_sync(0xffffffffu, any == 0)) break;
    }
}

constexpr float SCALE_LOG2E = 0.0625f * 1.4426950408889634f;

__global__ void __launch_bounds__(NTHREADS, 1) gated_mix_decode_kernel(const __grid_constant__ Params p) {
    extern __shared__ __align__(1024) char smem[];
    uint32_t due;
    asm volatile("mov.u32 %0, %globaltimer_lo;" : "=r"(due));
    const uint32_t sb = (uint32_t)__cvta_generic_to_shared(smem);
    const uint32_t bars = sb + OFF_BAR;
    const uint32_t tid = threadIdx.x, lane = tid & 31;
    const uint32_t cta = blockIdx.x, head = cta >> 4, j = cta & 15;
    const uint32_t mi = lane >> 3, r = lane & 7;

    if (tid < 224) {
        const char* src = p.wq[j >> 3] + ((tid >> 3) * (16 * 8192) + head * 1024 + (j & 7) * 128 + r * 16);
        uint32_t dst = sb + OFF_W + (tid >> 3) * (16 * 128) + 16 * (r ^ (2 * mi));
#pragma unroll 1
        for (int i = 0; i < 8; i++) {
            asm volatile("cp.async.cg.shared.global.L2::cache_hint [%0], [%1], 16, %2;"
                         ::"r"(dst), "l"(src), "l"(EVICT_FIRST) : "memory");
            asm volatile("cp.async.cg.shared.global.L2::cache_hint [%0], [%1], 16, %2;"
                         ::"r"(dst ^ (128 + 16)), "l"(src + 8192), "l"(EVICT_FIRST) : "memory");
            dst += 256;
            src += 16384;
        }
    }
    const uint32_t warp = __shfl_sync(0xffffffffu, tid >> 5, 0);
    const uint32_t g = lane >> 2, t = lane & 3;

    if (warp == 9) {
        char* const sc = (char*)p.sc;
        void* const qdst = sc + (uint32_t)(offsetof(Scratch, q) + cta * 256 + (t * 8 + g) * 8);
        put2(qdst, 0u, 0u);
        uint32_t tag;
        asm volatile("ld.relaxed.gpu.global.u32 %0, [%1];" : "=r"(tag) : "l"(&p.sc->epoch) : "memory");
        tag++;
        *(uint32_t*)(smem + OFF_TAG) = tag;
        asm volatile("bar.sync 0, 320;" ::: "memory");
        {
            float q0 = 0.f, q1 = 0.f;
#pragma unroll 1
            for (int w = 0; w < 7; w++) {
                const float4 f = *(const float4*)(smem + OFF_S + (w * 32 + lane) * 16);
                q0 += f.x; q1 += f.z;
            }
            put2(qdst, pack_bf2(0.f, q0) | tag, pack_bf2(0.f, q1) | tag);
        }
        {
            float z = 0.f;
#pragma unroll 1
            for (uint32_t i = lane; i < DM / 4; i += 32) {
                const uint2 a = __ldg((const uint2*)p.x + i), b = __ldg((const uint2*)p.gw + i);
                uint32_t m0, m1;
                asm("mul.rn.bf16x2 %0, %1, %2;" : "=r"(m0) : "r"(a.x), "r"(b.x));
                asm("mul.rn.bf16x2 %0, %1, %2;" : "=r"(m1) : "r"(a.y), "r"(b.y));
                z += (bf_lo(m0) + bf_hi(m0)) + (bf_lo(m1) + bf_hi(m1));
            }
#pragma unroll 1
            for (int s = 16; s; s >>= 1) z += shx(z, s);
            const float gate = round_bf(rcp(1.f + ex2(round_bf(z) * -1.4426950408889634f)));
            *(float2*)(smem + OFF_TAG + 8) = make_float2(gate, round_bf(1.f - gate));
        }
#pragma unroll 1
        for (int br = 0; br < 2; br++) {
            mbar_wait(bars + 8 * (B_ML + br));
            float m = ((const float*)(smem + OFF_M))[br * 16 + (lane & 15)];
            float l = ((const float*)(smem + OFF_L))[br * 16 + (lane & 15)];
#pragma unroll
            for (int s = 1; s < 8; s <<= 1) { m = fmaxf(m, shx(m, s)); l += shx(l, s); }
            if (r == 0) put2(sc + (uint32_t)(offsetof(Scratch, ml) + br * 4096 + cta * 32 + lane), tagged(m, tag), tagged(l, tag));
        }
#pragma unroll 1
        for (int br = 0; br < 2; br++) {
            uint4 ml[1] = {}, v[4] = {};
            gather<1>(ml, sc + (uint32_t)(offsetof(Scratch, ml) + br * 4096 + head * 512 + (lane & 15) * 32), tag);
            const float m = untag((j & 8) ? ml[0].z : ml[0].x);
            float M = m;
#pragma unroll
            for (int s = 8; s; s >>= 1) M = fmaxf(M, shx(M, s));
            const float e = ex2((m - M) * SCALE_LOG2E);
            float L = e * untag((j & 8) ? ml[0].w : ml[0].y);
#pragma unroll
            for (int s = 8; s; s >>= 1) L += shx(L, s);
            const float wgt = e * rcp(L);
            float wk[4];
#pragma unroll
            for (int k = 0; k < 4; k++) wk[k] = __shfl_sync(0xffffffffu, wgt, 4 * k + mi);
            if (br) {
                mbar_wait(bars + 8 * (B_FULL + OWAIT));
                if (ODELAY) __nanosleep(ODELAY);
            }
            gather<4>(v, sc + (uint32_t)(offsetof(Scratch, o) + br * sizeof(Scratch::o[0]) + cta * 2048 + lane * 16), tag);
            float o0 = 0.f, o1 = 0.f, o2 = 0.f, o3 = 0.f;
#pragma unroll
            for (int k = 0; k < 4; k++) {
                o0 = fmaf(wk[k], untag(v[k].x), o0); o1 = fmaf(wk[k], untag(v[k].y), o1);
                o2 = fmaf(wk[k], untag(v[k].z), o2); o3 = fmaf(wk[k], untag(v[k].w), o3);
            }
            const bool h1 = lane & 8, h2 = lane & 16;
            const float b0 = (h1 ? o2 : o0) + shx(h1 ? o0 : o2, 8);
            const float b1 = (h1 ? o3 : o1) + shx(h1 ? o1 : o3, 8);
            const float od = (h2 ? b1 : b0) + shx(h2 ? b0 : b1, 16);
            const uint32_t d = 4 * (lane & 4) + 2 * t + ((lane >> 3) & 1) + ((lane & 16) >> 1);
            ((unsigned short*)(smem + OFF_O))[br * 32 + d] = (unsigned short)pack_bf2(od, 0.f);
            __syncwarp();
            if (lane == 0) mbar_arrive(bars + 8 * (B_OREADY + br));
            if (lane == 0) STAMP(5 + 3 * br);
        }
    } else if (warp == 8) {
        if (lane == 0) {
#pragma unroll 6
            for (int i = 0; i < NBAR1; i++) {
                asm volatile("mbarrier.init.shared::cta.b64 [%0], 1;" ::"r"(bars + 8 * i) : "memory");
                asm volatile("mbarrier.init.shared::cta.b64 [%0], 8;" ::"r"(bars + 8 * (NBAR1 + i)) : "memory");
            }
            asm volatile("fence.mbarrier_init.release.cluster;" ::: "memory");
        }
        __syncwarp();
        asm volatile("bar.arrive 0, 320;" ::: "memory");
        if (lane == 0) {
            due += RATE0 + STAG * cta;
            uint32_t i = 0;
#pragma unroll 1
            for (int s = 0; s < 6; s++) {
                const bool kv = s < 4;
                const char* src = p.seg[s] + (kv ? head * (SK * 512) + j * TILE : cta * (2 * WOT));
                const uint32_t end = i + (kv ? (s < 2 ? NA : NB) : 2);
                const uint32_t bytes = kv ? TILE : WOT;
#pragma unroll 1
                for (; i < end; i++) {
                    const uint32_t full = bars + 8 * (B_FULL + i);
                    if (kv && i >= NS) mbar_wait(full + 8 * (B_EMPTY - NS));
                    if (i >= WIN) mbar_wait(full - 8 * WIN);
                    while (true) {
                        uint32_t now, ok;
                        asm volatile("mov.u32 %0, %globaltimer_lo;" : "=r"(now));
                        asm volatile("{\n.reg .pred p;\nmbarrier.test_wait.parity.shared::cta.b64 p, [%1], 0;\nselp.u32 %0, 1, 0, p;\n}\n"
                                     : "=r"(ok) : "r"(i >= WMIN ? full - 8 * WMIN : full) : "memory");
                        if ((int)(now - due) >= 0 || ok) break;
                    }
                    asm volatile("mbarrier.arrive.expect_tx.shared::cta.b64 _, [%0], %1;" ::"r"(full), "r"(bytes) : "memory");
                    asm volatile("cp.async.bulk.shared::cluster.global.mbarrier::complete_tx::bytes.L2::cache_hint [%0], [%1], %2, [%3], %4;"
                                 ::"r"(kv ? sb + OFF_RING + (i % NS) * TILE : sb + OFF_W + (i - NKV) * WOT), "l"(src),
                                   "r"(bytes), "r"(full), "l"(EVICT_FIRST) : "memory");
                    src += kv ? 16 * TILE : WOT;
                    due += kv ? RATE : WORATE;
                }
            }
        }
    } else {
        char* const sc = (char*)p.sc;
        char* odst = sc + (uint32_t)(offsetof(Scratch, o) + (head * 16 + (t >> 1) * 8 + warp) * 2048 + j * 128 + ((t & 1) * 8 + g) * 8);
        put2(odst + sizeof(Scratch::o[0]), 0u, 0u);
        if (warp < 7) {
            uint32_t xb[8];
            asm volatile("ld.global.nc.v4.u32 {%0, %1, %2, %3}, [%8];\nld.global.nc.v4.u32 {%4, %5, %6, %7}, [%8 + 16];\n"
                         "cp.async.wait_all;"
                         : "=r"(xb[0]), "=r"(xb[1]), "=r"(xb[2]), "=r"(xb[3]), "=r"(xb[4]), "=r"(xb[5]), "=r"(xb[6]), "=r"(xb[7])
                         : "l"(p.x + (warp * 128 + t * 32)) : "memory");
            __syncwarp();
            const uint32_t a0 = sb + OFF_W + (warp * 64 + 16 * (r >> 1) + 2 * (mi >> 1) + (r & 1)) * 128 + 16 * ((mi & 1) ^ r);
#pragma unroll 1
            for (uint32_t i = 0; i < 4; i++) {
                float c[4] = {0.f, 0.f, 0.f, 0.f};
#pragma unroll
                for (int ks = 0; ks < 4; ks++) {
                    uint32_t a[4];
                    ldsm4t(a, (a0 ^ (32 * i)) + ks * 512);
                    mma16816(c, a, xb[2 * ks], xb[2 * ks + 1]);
                }
                if (t == i) *(float4*)(smem + OFF_S + tid * 16) = make_float4(c[0], c[1], c[2], c[3]);
            }
            asm volatile("fence.proxy.async.shared::cta;" ::: "memory");
        }
        asm volatile("bar.sync 0, 320;" ::: "memory");
        if (tid == 0) STAMP(1);
        const uint32_t tag = *(const uint32_t*)(smem + OFF_TAG);

        const bool valid = t == (g & 3);
        const uint32_t lm0 = sb + OFF_RING + (8 * (mi >> 1) + r) * 512 + 16 * ((mi & 1) ^ (r >> 1));
        const uint32_t lm1 = lm0 ^ 32;
        {
            if (QDELAY) __nanosleep(QDELAY);
            uint4 v[1] = {};
            gather<1>(v, sc + (uint32_t)(offsetof(Scratch, q) + head * 4096 + tid * 16), tag);
            uint32_t* qs = (uint32_t*)(smem + OFF_Q + (warp >> 1) * QS + (warp & 1) * 256) + g * 8 + t;
            qs[0] = __byte_perm(v[0].x, v[0].z, 0x7632);
            qs[4] = __byte_perm(v[0].y, v[0].w, 0x7632);
            asm volatile("bar.sync 1, 256;" ::: "memory");
        }
        if (tid == 0) STAMP(2);
        uint32_t qa[16][4];
        {
            const uint32_t q0 = sb + OFF_Q + ((mi & 1) * 2 + (r >> 2)) * QS + 16 * ((mi >> 1) ^ (r & 3));
#pragma unroll
            for (int k = 0; k < 16; k++) ldsm4(qa[k], (q0 ^ ((k & 1) * 32)) + 64 * (k >> 1));
        }
        uint32_t T0 = 0;
#pragma unroll 1
        for (int br = 0; br < 2; br++) {
            const uint32_t nt = br ? NB : NA;
            float mx = -INFINITY;
#pragma unroll 1
            for (uint32_t kt = warp >> 1; kt < nt; kt += 4) {
                const uint32_t T = T0 + kt, off = (T % NS) * TILE + (warp & 1) * 8192;
                mbar_wait(bars + 8 * (B_FULL + T));
                float c0[4] = {0.f, 0.f, 0.f, 0.f}, c1[4] = {0.f, 0.f, 0.f, 0.f};
#pragma unroll
                for (int k = 0; k < 16; k++) {
                    uint32_t b[4];
                    ldsm4(b, ((k & 1) ? lm1 : lm0) + off + 64 * (k >> 1));
                    mma16816(c0, qa[k], b[0], b[1]);
                    mma16816(c1, qa[k], b[2], b[3]);
                }
                __syncwarp();
                if (lane == 0) asm volatile("mbarrier.arrive.shared::cta.b64 _, [%0], 4;" ::"r"(bars + 8 * (B_EMPTY + T)) : "memory");
                float4 s;
                s.x = round_bf(br ? c0[2] : c0[0]); s.y = round_bf(br ? c0[3] : c0[1]);
                s.z = round_bf(br ? c1[2] : c1[0]); s.w = round_bf(br ? c1[3] : c1[1]);
                if (valid) *(float4*)(smem + OFF_S + ((2 * kt + (warp & 1)) * 8 + g) * 16) = s;
                mx = fmaxf(fmaxf(mx, fmaxf(s.x, s.y)), fmaxf(s.z, s.w));
            }
            mx = fmaxf(mx, shx(mx, 5));
            mx = fmaxf(mx, shx(mx, 10));
            float* mred = (float*)(smem + OFF_M) + br * 16;
            if ((lane & 15) == 0) mred[(lane >> 1) + warp] = mx;
            asm volatile("bar.sync 1, 256;" ::: "memory");
            if (tid == 0) STAMP(3 + 3 * br);
            {
                const float4 m0 = *(const float4*)(mred + (lane & 4) * 2), m1 = *(const float4*)(mred + (lane & 4) * 2 + 4);
                const float M = fmaxf(fmaxf(fmaxf(m0.x, m0.y), fmaxf(m0.z, m0.w)), fmaxf(fmaxf(m1.x, m1.y), fmaxf(m1.z, m1.w)));
                const float4 s = *(const float4*)(smem + OFF_S + tid * 16);
                const uint32_t p0 = pack_bf2(ex2((s.x - M) * SCALE_LOG2E), ex2((s.y - M) * SCALE_LOG2E));
                const uint32_t p1 = pack_bf2(ex2((s.z - M) * SCALE_LOG2E), ex2((s.w - M) * SCALE_LOG2E));
                *(uint2*)(smem + OFF_P + ((tid >> 4) * 8 + r) * 16 + (tid & 8)) = make_uint2(p0, p1);
                float l = (bf_lo(p0) + bf_hi(p0)) + (bf_lo(p1) + bf_hi(p1));
                l += shx(l, 1); l += shx(l, 2); l += shx(l, 8); l += shx(l, 16);
                if ((lane & ~4) == 0) mred[(OFF_L - OFF_M) / 4 + lane * 2 + warp] = tid < nt * 16 ? l : 0.f;
            }
            asm volatile("bar.sync 1, 256;" ::: "memory");
            if (tid == 0) mbar_arrive(bars + 8 * (B_ML + br));
            T0 += nt;
            float o0[4] = {0.f, 0.f, 0.f, 0.f}, o1[4] = {0.f, 0.f, 0.f, 0.f};
#pragma unroll 1
            for (uint32_t vt = 0; vt < nt; vt++) {
                const uint32_t T = T0 + vt, off = (T % NS) * TILE + warp * 64;
                uint4 pb = make_uint4(0u, 0u, 0u, 0u);
                if (valid) pb = *(const uint4*)(smem + OFF_P + (vt * 8 + g) * 16);
                mbar_wait(bars + 8 * (B_FULL + T));
                uint32_t a[4][4];
                ldsm4t(a[0], lm0 + off);
                ldsm4t(a[1], lm1 + off);
                ldsm4t(a[2], lm0 + off + 8192);
                ldsm4t(a[3], lm1 + off + 8192);
                mma16816(o0, a[0], pb.x, pb.y);
                mma16816(o1, a[1], pb.x, pb.y);
                mma16816(o0, a[2], pb.z, pb.w);
                mma16816(o1, a[3], pb.z, pb.w);
                __syncwarp();
                if (lane == 0) mbar_arrive(bars + 8 * (B_EMPTY + T));
            }
            T0 += nt;
            if (tid == 0) STAMP(4 + 3 * br);
            const float u0 = o0[0] + o0[3] + shx(o1[0] + o1[3], 1);
            const float u1 = o0[2] + o0[1] + shx(o1[2] + o1[1], 1);
            put2(odst, tagged(u0, tag), tagged(u1, tag));
            odst += sizeof(Scratch::o[0]);
        }
        if (warp < 7) {
            uint32_t wm = sb + OFF_W + (8 * (mi >> 1) + r) * (DM * 2) + 128 * warp + 16 * ((mi & 1) ^ r);
            const uint32_t msk = (g >> 1) != t ? 0u : (g & 1) ? 0xffff0000u : 0x0000ffffu;
            char* ap = sc + ((tid >> 3) * 1024 + (tid & 4) * 64 + t * 16);
            unsigned short* op = p.out + (64 * warp + 16 * t + g);
            float y0 = 0.f, y1 = 0.f;
#pragma unroll 1
            for (int br = 0; br < 2; br++) {
                mbar_wait(bars + 8 * (B_OREADY + br));
                const float gb = *(const float*)(smem + OFF_TAG + 8 + 4 * br);
                uint32_t ob[4], a[2][4][4];
#pragma unroll
                for (int i = 0; i < 4; i++) ob[i] = ((const uint32_t*)(smem + OFF_O))[br * 16 + 4 * i + t] & msk;
#pragma unroll
                for (int x = 0; x < 2; x++) {
                    mbar_wait(bars + 8 * (B_FULL + NKV + 2 * br + x));
#pragma unroll
                    for (int i = 3; i >= 0; i--) ldsm4t(a[x][i], (wm ^ (32 * i)) + x * WOT);
                }
                float P[8];
#pragma unroll
                for (int i = 3; i >= 0; i--) {
                    float c[4] = {0.f, 0.f, 0.f, 0.f};
                    mma16816(c, a[0][i], ob[0], ob[1]);
                    mma16816(c, a[1][i], ob[2], ob[3]);
                    P[2 * i] = c[0] + c[3];
                    P[2 * i + 1] = c[2] + c[1];
                }
                y0 = fmaf(gb, shx(P[4] + shx(P[6], 1), 2), fmaf(gb, P[0] + shx(P[2], 1), y0));
                y1 = fmaf(gb, shx(P[5] + shx(P[7], 1), 2), fmaf(gb, P[1] + shx(P[3], 1), y1));
                wm += 2 * WOT;
            }
            asm volatile("{\n.reg .pred p, q;\n.reg .f32 n0, s0, s1, n1;\n.reg .b16 lo, hi;\n.reg .b32 w;\n"
                         "atom.relaxed.gpu.global.add.v4.f32 {n0, s0, s1, n1}, [%0], {%4, %2, %3, %4};\n"
                         "add.f32 s0, s0, %2;\nadd.f32 s1, s1, %3;\ncvt.rn.bf16x2.f32 w, s1, s0;\nmov.b32 {lo, hi}, w;\n"
                         "setp.eq.f32 p, n0, %5;\nsetp.eq.f32 q, n1, %5;\n"
                         "@p st.global.b16 [%1], lo;\n@q st.global.b16 [%1 + 16], hi;\n"
                         "@p st.relaxed.gpu.global.v2.b32 [%0], {0, 0};\n@q st.relaxed.gpu.global.v2.b32 [%0 + 8], {0, 0};\n"
                         "setp.eq.and.u32 p, %6, 0, p;\n@p st.relaxed.gpu.global.b32 [%0 + %8], %7;\n}\n"
                         ::"l"(ap), "l"(op), "f"(y0), "f"(y1), "f"(1.f), "f"((float)(NCTA - 1)), "r"(tid),
                           "r"(tag == TAGM ? 0u : tag), "n"(offsetof(Scratch, epoch)) : "memory");
            if (tid == 0) STAMP(15);
        }
    }
}

}

extern "C" void kernel_launch(void* const* d_in, const int* in_sizes, int n_in, void* d_out, int out_size) {
    (void)in_sizes; (void)n_in; (void)out_size;
    Params p;
    p.wq[0] = (const char*)d_in[3];
    p.wq[1] = (const char*)d_in[8];
    p.x = (const char*)d_in[0];
    p.gw = (const char*)d_in[10];
    p.seg[0] = (const char*)d_in[1] + (size_t)(SK - WA) * 512;
    p.seg[1] = (const char*)d_in[2] + (size_t)(SK - WA) * 512;
    p.seg[2] = (const char*)d_in[6];
    p.seg[3] = (const char*)d_in[7];
    p.seg[4] = (const char*)d_in[4];
    p.seg[5] = (const char*)d_in[9];
    p.out = (unsigned short*)d_out;
    void* sc = nullptr;
    cudaGetSymbolAddress(&sc, g_scratch);
    p.sc = (Scratch*)(((uintptr_t)sc + 32767) & ~(uintptr_t)32767);
    cudaFuncSetAttribute(gated_mix_decode_kernel, cudaFuncAttributeMaxDynamicSharedMemorySize, SMEM_BYTES);
    gated_mix_decode_kernel<<<NCTA, NTHREADS, SMEM_BYTES>>>(p);
}
```

```cpp
#include <cuda_runtime.h>
#include <cuda_bf16.h>
#include <stdint.h>
#include <stddef.h>

#define NS 10
#define WIN 5
#define WINE 3
#define WMIN 1
#define RATE 652
#define RATE0 1060
#define WORATE (RATE * 7 / 8)
#define STAG 5
#define PSHIFT 0
#define QDELAY 500
#define OWAIT 40
#define ODELAY 200

namespace {

constexpr int DM = 448;
constexpr int SK = 8192;
constexpr int WA = 2048;
constexpr int NCTA = 128;
constexpr int TILE = 16384;
constexpr int NA = 4, NB = 16;
constexpr int NKV = 2 * (NA + NB);
constexpr int NT = NKV + 4;
constexpr int WOT = 16 * DM * 2;
constexpr int NTHREADS = 320;
constexpr uint32_t SPIN_LIMIT = 1u << 18;
constexpr uint64_t EVICT_FIRST = 0x12F0000000000000ull;

constexpr int OFF_W    = 0;
constexpr int OFF_RING = 4 * WOT;
constexpr int QS = 576;
constexpr int OFF_Q    = OFF_RING + NS * TILE;
constexpr int OFF_S    = OFF_Q + 4 * QS;
constexpr int OFF_P    = OFF_S + 4096;
constexpr int OFF_M    = OFF_P + 2048;
constexpr int OFF_L    = OFF_M + 128;
constexpr int OFF_O    = OFF_L + 128;
constexpr int OFF_TAG  = OFF_O + 128;
constexpr int OFF_BAR  = OFF_TAG + 16;
constexpr int B_FULL = 0, B_ML = NT  , B_OREADY = B_ML + 2  , NBAR1 = B_OREADY + 2,
              B_EMPTY = NBAR1, NBAR = 2 * NBAR1;
constexpr int SMEM_BYTES = OFF_BAR + NBAR * 8;

constexpr uint32_t TAGM = 15u;
struct Scratch {
    float4 acc[2048];
    uint4 o[2][8][16][16][8];
    uint4 q[8][256];
    uint4 ml[2][8][16][2];
    unsigned int epoch;
};
__device__ uint4 g_scratch[(sizeof(Scratch) + 32768) / 16];

struct Params {
    const char* wq[2];
    const char *x, *gw;
    Scratch* sc;
    unsigned short* out;
    const char* seg[6];
};

#define STAMP(i)

__device__ __forceinline__ void mbar_arrive(uint32_t bar) {
    asm volatile("mbarrier.arrive.shared::cta.b64 _, [%0];" ::"r"(bar) : "memory");
}
__device__ __forceinline__ void mbar_wait(uint32_t bar) {
    asm volatile("{\n.reg .pred p, q;\n.reg .u32 n;\nmov.u32 n, 0;\n"
                 "W:\nmbarrier.try_wait.parity.shared::cta.b64 p, [%0], 0;\nadd.u32 n, n, 1;\n"
                 "setp.lt.and.u32 q, n, %1, !p;\n@q bra W;\n}\n" ::"r"(bar), "n"(SPIN_LIMIT) : "memory");
}
__device__ __forceinline__ void ldsm4(uint32_t (&r)[4], uint32_t a) {
    asm volatile("ldmatrix.sync.aligned.m8n8.x4.shared.b16 {%0,%1,%2,%3}, [%4];"
                 : "=r"(r[0]), "=r"(r[1]), "=r"(r[2]), "=r"(r[3]) : "r"(a) : "memory");
}
__device__ __forceinline__ void ldsm4t(uint32_t (&r)[4], uint32_t a) {
    asm volatile("ldmatrix.sync.aligned.m8n8.x4.trans.shared.b16 {%0,%1,%2,%3}, [%4];"
                 : "=r"(r[0]), "=r"(r[1]), "=r"(r[2]), "=r"(r[3]) : "r"(a) : "memory");
}
__device__ __forceinline__ void mma16816(float (&c)[4], const uint32_t (&a)[4], uint32_t b0, uint32_t b1) {
    asm("mma.sync.aligned.m16n8k16.row.col.f32.bf16.bf16.f32 {%0,%1,%2,%3}, {%4,%5,%6,%7}, {%8,%9}, {%0,%1,%2,%3};"
        : "+f"(c[0]), "+f"(c[1]), "+f"(c[2]), "+f"(c[3])
        : "r"(a[0]), "r"(a[1]), "r"(a[2]), "r"(a[3]), "r"(b0), "r"(b1));
}
__device__ __forceinline__ float bf_lo(uint32_t v) { return __uint_as_float(v << 16); }
__device__ __forceinline__ float bf_hi(uint32_t v) { return __uint_as_float(v & 0xffff0000u); }
__device__ __forceinline__ uint32_t pack_bf2(float lo, float hi) {
    uint32_t r;
    asm("cvt.rn.bf16x2.f32 %0, %1, %2;" : "=r"(r) : "f"(hi), "f"(lo));
    return r;
}
__device__ __forceinline__ float round_bf(float v) { return __uint_as_float(pack_bf2(0.f, v)); }
__device__ __forceinline__ float ex2(float v) {
    float r;
    asm("ex2.approx.ftz.f32 %0, %1;" : "=f"(r) : "f"(v));
    return r;
}
__device__ __forceinline__ float rcp(float v) {
    float r;
    asm("rcp.approx.ftz.f32 %0, %1;" : "=f"(r) : "f"(v));
    return r;
}
__device__ __forceinline__ float shx(float v, int m) { return __shfl_xor_sync(0xffffffffu, v, m); }
__device__ __forceinline__ uint32_t tagged(float v, uint32_t tag) { return (__float_as_uint(v) & ~TAGM) | tag; }
__device__ __forceinline__ float untag(uint32_t v) { return __uint_as_float(v & ~TAGM); }
__device__ __forceinline__ void put2(void* p, uint32_t a, uint32_t b) {
    asm volatile("st.relaxed.gpu.global.v2.b32 [%0], {%1, %2};" ::"l"(p), "r"(a), "r"(b) : "memory");
}
template <int N>
__device__ __forceinline__ void gather(uint4 (&v)[N], const void* p, uint32_t tag) {
    uint32_t need[N];
#pragma unroll
    for (int k = 0; k < N; k++) need[k] = 1;
#pragma unroll 1
    for (uint32_t n = 0; n < SPIN_LIMIT; n++) {
#pragma unroll
        for (int k = 0; k < N; k++)
            asm volatile("{\n.reg .pred p;\nsetp.ne.u32 p, %5, 0;\n@p ld.relaxed.gpu.global.v4.b32 {%0, %1, %2, %3}, [%4];\n}\n"
                         : "+r"(v[k].x), "+r"(v[k].y), "+r"(v[k].z), "+r"(v[k].w)
                         : "l"((const char*)p + 512 * k), "r"(need[k]) : "memory");
        uint32_t any = 0;
#pragma unroll
        for (int k = 0; k < N; k++) {
            need[k] = ((v[k].x ^ tag) | (v[k].y ^ tag) | (v[k].z ^ tag) | (v[k].w ^ tag)) & TAGM;
            any |= need[k];
        }
        if (__all_sync(0xffffffffu, any == 0)) break;
    }
}

constexpr float SCALE_LOG2E = 0.0625f * 1.4426950408889634f;

__global__ void __launch_bounds__(NTHREADS, 1) gated_mix_decode_kernel(const __grid_constant__ Params p) {
    extern __shared__ __align__(1024) char smem[];
    asm volatile("prefetch.global.L2 [%0];" ::"l"(p.wq[0] + (blockIdx.x * NTHREADS + threadIdx.x) * 32));
    const uint32_t sb = (uint32_t)__cvta_generic_to_shared(smem);
    const uint32_t bars = sb + OFF_BAR;
    const uint32_t tid = threadIdx.x, lane = tid & 31;
    const uint32_t cta = blockIdx.x, head = cta >> 4, j = cta & 15;
    const uint32_t mi = lane >> 3, r = lane & 7;

    if (tid < 224) {
        const char* src = p.wq[j >> 3] + ((tid >> 3) * (16 * 8192) + head * 1024 + (j & 7) * 128 + r * 16);
        uint32_t dst = sb + OFF_W + (tid >> 3) * (16 * 128) + 16 * (r ^ (2 * mi));
#pragma unroll 1
        for (int i = 0; i < 8; i++) {
            asm volatile("cp.async.cg.shared.global.L2::cache_hint [%0], [%1], 16, %2;"
                         ::"r"(dst), "l"(src), "l"(EVICT_FIRST) : "memory");
            asm volatile("cp.async.cg.shared.global.L2::cache_hint [%0], [%1], 16, %2;"
                         ::"r"(dst ^ (128 + 16)), "l"(src + 8192), "l"(EVICT_FIRST) : "memory");
            dst += 256;
            src += 16384;
        }
    }
    uint32_t due;
    asm volatile("mov.u32 %0, %globaltimer_lo;" : "=r"(due));
    const uint32_t warp = __shfl_sync(0xffffffffu, tid >> 5, 0);
    const uint32_t g = lane >> 2, t = lane & 3;

    if (warp == 9) {
        char* const sc = (char*)p.sc;
        void* const qdst = sc + (uint32_t)(offsetof(Scratch, q) + cta * 256 + (t * 8 + g) * 8);
        put2(qdst, 0u, 0u);
        uint32_t tag;
        asm volatile("ld.relaxed.gpu.global.u32 %0, [%1];" : "=r"(tag) : "l"(&p.sc->epoch) : "memory");
        tag++;
        *(uint32_t*)(smem + OFF_TAG) = tag;
        asm volatile("bar.sync 0, 320;" ::: "memory");
        {
            float q0 = 0.f, q1 = 0.f;
#pragma unroll 1
            for (int w = 0; w < 7; w++) {
                const float4 f = *(const float4*)(smem + OFF_S + (w * 32 + lane) * 16);
                q0 += f.x; q1 += f.z;
            }
            put2(qdst, pack_bf2(0.f, q0) | tag, pack_bf2(0.f, q1) | tag);
        }
        {
            float z = 0.f;
#pragma unroll 1
            for (uint32_t i = lane; i < DM / 4; i += 32) {
                const uint2 a = __ldg((const uint2*)p.x + i), b = __ldg((const uint2*)p.gw + i);
                uint32_t m0, m1;
                asm("mul.rn.bf16x2 %0, %1, %2;" : "=r"(m0) : "r"(a.x), "r"(b.x));
                asm("mul.rn.bf16x2 %0, %1, %2;" : "=r"(m1) : "r"(a.y), "r"(b.y));
                z += (bf_lo(m0) + bf_hi(m0)) + (bf_lo(m1) + bf_hi(m1));
            }
#pragma unroll 1
            for (int s = 16; s; s >>= 1) z += shx(z, s);
            const float gate = round_bf(rcp(1.f + ex2(round_bf(z) * -1.4426950408889634f)));
            *(float2*)(smem + OFF_TAG + 8) = make_float2(gate, round_bf(1.f - gate));
        }
#pragma unroll 1
        for (int br = 0; br < 2; br++) {
            mbar_wait(bars + 8 * (B_ML + br));
            float m = ((const float*)(smem + OFF_M))[br * 16 + (lane & 15)];
            float l = ((const float*)(smem + OFF_L))[br * 16 + (lane & 15)];
#pragma unroll
            for (int s = 1; s < 8; s <<= 1) { m = fmaxf(m, shx(m, s)); l += shx(l, s); }
            if (r == 0) put2(sc + (uint32_t)(offsetof(Scratch, ml) + br * 4096 + cta * 32 + lane), tagged(m, tag), tagged(l, tag));
        }
#pragma unroll 1
        for (int br = 0; br < 2; br++) {
            uint4 ml[1] = {}, v[4] = {};
            gather<1>(ml, sc + (uint32_t)(offsetof(Scratch, ml) + br * 4096 + head * 512 + (lane & 15) * 32), tag);
            const float m = untag((j & 8) ? ml[0].z : ml[0].x);
            float M = m;
#pragma unroll
            for (int s = 8; s; s >>= 1) M = fmaxf(M, shx(M, s));
            const float e = ex2((m - M) * SCALE_LOG2E);
            float L = e * untag((j & 8) ? ml[0].w : ml[0].y);
#pragma unroll
            for (int s = 8; s; s >>= 1) L += shx(L, s);
            const float wgt = e * rcp(L);
            float wk[4];
#pragma unroll
            for (int k = 0; k < 4; k++) wk[k] = __shfl_sync(0xffffffffu, wgt, 4 * k + mi);
            if (br) {
                mbar_wait(bars + 8 * (B_FULL + OWAIT));
                if (ODELAY) __nanosleep(ODELAY);
            }
            gather<4>(v, sc + (uint32_t)(offsetof(Scratch, o) + br * sizeof(Scratch::o[0]) + cta * 2048 + lane * 16), tag);
            float o0 = 0.f, o1 = 0.f, o2 = 0.f, o3 = 0.f;
#pragma unroll
            for (int k = 0; k < 4; k++) {
                o0 = fmaf(wk[k], untag(v[k].x), o0); o1 = fmaf(wk[k], untag(v[k].y), o1);
                o2 = fmaf(wk[k], untag(v[k].z), o2); o3 = fmaf(wk[k], untag(v[k].w), o3);
            }
            const bool h1 = lane & 8, h2 = lane & 16;
            const float b0 = (h1 ? o2 : o0) + shx(h1 ? o0 : o2, 8);
            const float b1 = (h1 ? o3 : o1) + shx(h1 ? o1 : o3, 8);
            const float od = (h2 ? b1 : b0) + shx(h2 ? b0 : b1, 16);
            const uint32_t d = 4 * (lane & 4) + 2 * t + ((lane >> 3) & 1) + ((lane & 16) >> 1);
            ((unsigned short*)(smem + OFF_O))[br * 32 + d] = (unsigned short)pack_bf2(od, 0.f);
            __syncwarp();
            if (lane == 0) mbar_arrive(bars + 8 * (B_OREADY + br));
            if (lane == 0) STAMP(5 + 3 * br);
        }
    } else if (warp == 8) {
        if (lane == 0) {
#pragma unroll 6
            for (int i = 0; i < NBAR1; i++) {
                asm volatile("mbarrier.init.shared::cta.b64 [%0], 1;" ::"r"(bars + 8 * i) : "memory");
                asm volatile("mbarrier.init.shared::cta.b64 [%0], 8;" ::"r"(bars + 8 * (NBAR1 + i)) : "memory");
            }
            asm volatile("fence.mbarrier_init.release.cluster;" ::: "memory");
        }
        __syncwarp();
        asm volatile("bar.arrive 0, 320;" ::: "memory");
        if (lane == 0) {
            due += RATE0 + STAG * cta;
            uint32_t i = 0;
#pragma unroll 1
            for (int s = 0; s < 6; s++) {
                const bool kv = s < 4;
                const char* src = p.seg[s] + (kv ? head * (SK * 512) + j * TILE : cta * (2 * WOT));
                const uint32_t end = i + (kv ? (s < 2 ? NA : NB) : 2);
                const uint32_t bytes = kv ? TILE : WOT;
#pragma unroll 1
                for (; i < end; i++) {
                    const uint32_t full = bars + 8 * (B_FULL + i);
                    if (kv && i >= NS) mbar_wait(full + 8 * (B_EMPTY - NS));
                    if (i >= WIN) mbar_wait(full - 8 * (kv ? WIN : WINE));
                    while (true) {
                        uint32_t now, ok;
                        asm volatile("mov.u32 %0, %globaltimer_lo;" : "=r"(now));
                        asm volatile("{\n.reg .pred p;\nmbarrier.test_wait.parity.shared::cta.b64 p, [%1], 0;\nselp.u32 %0, 1, 0, p;\n}\n"
                                     : "=r"(ok) : "r"(i >= WMIN ? full - 8 * WMIN : full) : "memory");
                        if ((int)(now - due) >= 0 || ok) break;
                    }
                    asm volatile("mbarrier.arrive.expect_tx.shared::cta.b64 _, [%0], %1;" ::"r"(full), "r"(bytes) : "memory");
                    asm volatile("cp.async.bulk.shared::cluster.global.mbarrier::complete_tx::bytes.L2::cache_hint [%0], [%1], %2, [%3], %4;"
                                 ::"r"(kv ? sb + OFF_RING + (i % NS) * TILE : sb + OFF_W + (i - NKV) * WOT), "l"(PSHIFT && kv ? src + ((i + PSHIFT * head) & (s < 2 ? NA - 1 : NB - 1)) * (16 * TILE) : src),
                                   "r"(bytes), "r"(full), "l"(EVICT_FIRST) : "memory");
                    src += kv ? (PSHIFT ? 0 : 16 * TILE) : WOT;
                    due += kv ? RATE : WORATE;
                }
            }
        }
    } else {
        char* const sc = (char*)p.sc;
        char* odst = sc + (uint32_t)(offsetof(Scratch, o) + (head * 16 + (t >> 1) * 8 + warp) * 2048 + j * 128 + ((t & 1) * 8 + g) * 8);
        put2(odst + sizeof(Scratch::o[0]), 0u, 0u);
        if (warp < 7) {
            uint32_t xb[8];
            asm volatile("ld.global.nc.v4.u32 {%0, %1, %2, %3}, [%8];\nld.global.nc.v4.u32 {%4, %5, %6, %7}, [%8 + 16];\n"
                         "cp.async.wait_all;"
                         : "=r"(xb[0]), "=r"(xb[1]), "=r"(xb[2]), "=r"(xb[3]), "=r"(xb[4]), "=r"(xb[5]), "=r"(xb[6]), "=r"(xb[7])
                         : "l"(p.x + (warp * 128 + t * 32)) : "memory");
            __syncwarp();
            const uint32_t a0 = sb + OFF_W + (warp * 64 + 16 * (r >> 1) + 2 * (mi >> 1) + (r & 1)) * 128 + 16 * ((mi & 1) ^ r);
#pragma unroll 1
            for (uint32_t i = 0; i < 4; i++) {
                float c[4] = {0.f, 0.f, 0.f, 0.f};
#pragma unroll
                for (int ks = 0; ks < 4; ks++) {
                    uint32_t a[4];
                    ldsm4t(a, (a0 ^ (32 * i)) + ks * 512);
                    mma16816(c, a, xb[2 * ks], xb[2 * ks + 1]);
                }
                if (t == i) *(float4*)(smem + OFF_S + tid * 16) = make_float4(c[0], c[1], c[2], c[3]);
            }
            asm volatile("fence.proxy.async.shared::cta;" ::: "memory");
        }
        asm volatile("bar.sync 0, 320;" ::: "memory");
        if (tid == 0) STAMP(1);
        const uint32_t tag = *(const uint32_t*)(smem + OFF_TAG);

        const bool valid = t == (g & 3);
        const uint32_t lm0 = sb + OFF_RING + (8 * (mi >> 1) + r) * 512 + 16 * ((mi & 1) ^ (r >> 1));
        const uint32_t lm1 = lm0 ^ 32;
        {
            if (QDELAY) __nanosleep(QDELAY);
            uint4 v[1] = {};
            gather<1>(v, sc + (uint32_t)(offsetof(Scratch, q) + head * 4096 + tid * 16), tag);
            uint32_t* qs = (uint32_t*)(smem + OFF_Q + (warp >> 1) * QS + (warp & 1) * 256) + g * 8 + t;
            qs[0] = __byte_perm(v[0].x, v[0].z, 0x7632);
            qs[4] = __byte_perm(v[0].y, v[0].w, 0x7632);
            asm volatile("bar.sync 1, 256;" ::: "memory");
        }
        if (tid == 0) STAMP(2);
        uint32_t qa[16][4];
        {
            const uint32_t q0 = sb + OFF_Q + ((mi & 1) * 2 + (r >> 2)) * QS + 16 * ((mi >> 1) ^ (r & 3));
#pragma unroll
            for (int k = 0; k < 16; k++) ldsm4(qa[k], (q0 ^ ((k & 1) * 32)) + 64 * (k >> 1));
        }
        uint32_t T0 = 0;
#pragma unroll 1
        for (int br = 0; br < 2; br++) {
            const uint32_t nt = br ? NB : NA;
            float mx = -INFINITY;
#pragma unroll 1
            for (uint32_t kt = warp >> 1; kt < nt; kt += 4) {
                const uint32_t T = T0 + kt, off = (T % NS) * TILE + (warp & 1) * 8192;
                mbar_wait(bars + 8 * (B_FULL + T));
                float c0[4] = {0.f, 0.f, 0.f, 0.f}, c1[4] = {0.f, 0.f, 0.f, 0.f};
#pragma unroll
                for (int k = 0; k < 16; k++) {
                    uint32_t b[4];
                    ldsm4(b, ((k & 1) ? lm1 : lm0) + off + 64 * (k >> 1));
                    mma16816(c0, qa[k], b[0], b[1]);
                    mma16816(c1, qa[k], b[2], b[3]);
                }
                __syncwarp();
                if (lane == 0) asm volatile("mbarrier.arrive.shared::cta.b64 _, [%0], 4;" ::"r"(bars + 8 * (B_EMPTY + T)) : "memory");
                float4 s;
                s.x = round_bf(br ? c0[2] : c0[0]); s.y = round_bf(br ? c0[3] : c0[1]);
                s.z = round_bf(br ? c1[2] : c1[0]); s.w = round_bf(br ? c1[3] : c1[1]);
                if (valid) *(float4*)(smem + OFF_S + ((2 * kt + (warp & 1)) * 8 + g) * 16) = s;
                mx = fmaxf(fmaxf(mx, fmaxf(s.x, s.y)), fmaxf(s.z, s.w));
            }
            mx = fmaxf(mx, shx(mx, 5));
            mx = fmaxf(mx, shx(mx, 10));
            float* mred = (float*)(smem + OFF_M) + br * 16;
            if ((lane & 15) == 0) mred[(lane >> 1) + warp] = mx;
            asm volatile("bar.sync 1, 256;" ::: "memory");
            if (tid == 0) STAMP(3 + 3 * br);
            {
                const float4 m0 = *(const float4*)(mred + (lane & 4) * 2), m1 = *(const float4*)(mred + (lane & 4) * 2 + 4);
                const float M = fmaxf(fmaxf(fmaxf(m0.x, m0.y), fmaxf(m0.z, m0.w)), fmaxf(fmaxf(m1.x, m1.y), fmaxf(m1.z, m1.w)));
                const float4 s = *(const float4*)(smem + OFF_S + tid * 16);
                const uint32_t p0 = pack_bf2(ex2((s.x - M) * SCALE_LOG2E), ex2((s.y - M) * SCALE_LOG2E));
                const uint32_t p1 = pack_bf2(ex2((s.z - M) * SCALE_LOG2E), ex2((s.w - M) * SCALE_LOG2E));
                *(uint2*)(smem + OFF_P + ((tid >> 4) * 8 + r) * 16 + (tid & 8)) = make_uint2(p0, p1);
                float l = (bf_lo(p0) + bf_hi(p0)) + (bf_lo(p1) + bf_hi(p1));
                l += shx(l, 1); l += shx(l, 2); l += shx(l, 8); l += shx(l, 16);
                if ((lane & ~4) == 0) mred[(OFF_L - OFF_M) / 4 + lane * 2 + warp] = tid < nt * 16 ? l : 0.f;
            }
            asm volatile("bar.sync 1, 256;" ::: "memory");
            if (tid == 0) mbar_arrive(bars + 8 * (B_ML + br));
            T0 += nt;
            float o0[4] = {0.f, 0.f, 0.f, 0.f}, o1[4] = {0.f, 0.f, 0.f, 0.f};
#pragma unroll 1
            for (uint32_t vt = 0; vt < nt; vt++) {
                const uint32_t T = T0 + vt, off = (T % NS) * TILE + warp * 64;
                uint4 pb = make_uint4(0u, 0u, 0u, 0u);
                if (valid) pb = *(const uint4*)(smem + OFF_P + (vt * 8 + g) * 16);
                mbar_wait(bars + 8 * (B_FULL + T));
                uint32_t a[4][4];
                ldsm4t(a[0], lm0 + off);
                ldsm4t(a[1], lm1 + off);
                ldsm4t(a[2], lm0 + off + 8192);
                ldsm4t(a[3], lm1 + off + 8192);
                mma16816(o0, a[0], pb.x, pb.y);
                mma16816(o1, a[1], pb.x, pb.y);
                mma16816(o0, a[2], pb.z, pb.w);
                mma16816(o1, a[3], pb.z, pb.w);
                __syncwarp();
                if (lane == 0) mbar_arrive(bars + 8 * (B_EMPTY + T));
            }
            T0 += nt;
            if (tid == 0) STAMP(4 + 3 * br);
            const float u0 = o0[0] + o0[3] + shx(o1[0] + o1[3], 1);
            const float u1 = o0[2] + o0[1] + shx(o1[2] + o1[1], 1);
            put2(odst, tagged(u0, tag), tagged(u1, tag));
            odst += sizeof(Scratch::o[0]);
        }
        if (warp < 7) {
            uint32_t wm = sb + OFF_W + (8 * (mi >> 1) + r) * (DM * 2) + 128 * warp + 16 * ((mi & 1) ^ r);
            const uint32_t msk = (g >> 1) != t ? 0u : (g & 1) ? 0xffff0000u : 0x0000ffffu;
            char* ap = sc + ((tid >> 3) * 1024 + (tid & 4) * 64 + t * 16);
            unsigned short* op = p.out + (64 * warp + 16 * t + g);
            float y0 = 0.f, y1 = 0.f;
#pragma unroll 1
            for (int br = 0; br < 2; br++) {
                mbar_wait(bars + 8 * (B_OREADY + br));
                const float gb = *(const float*)(smem + OFF_TAG + 8 + 4 * br);
                uint32_t ob[4], a[2][4][4];
#pragma unroll
                for (int i = 0; i < 4; i++) ob[i] = ((const uint32_t*)(smem + OFF_O))[br * 16 + 4 * i + t] & msk;
#pragma unroll
                for (int x = 0; x < 2; x++) {
                    mbar_wait(bars + 8 * (B_FULL + NKV + 2 * br + x));
#pragma unroll
                    for (int i = 3; i >= 0; i--) ldsm4t(a[x][i], (wm ^ (32 * i)) + x * WOT);
                }
                float P[8];
#pragma unroll
                for (int i = 3; i >= 0; i--) {
                    float c[4] = {0.f, 0.f, 0.f, 0.f};
                    mma16816(c, a[0][i], ob[0], ob[1]);
                    mma16816(c, a[1][i], ob[2], ob[3]);
                    P[2 * i] = c[0] + c[3];
                    P[2 * i + 1] = c[2] + c[1];
                }
                y0 = fmaf(gb, shx(P[4] + shx(P[6], 1), 2), fmaf(gb, P[0] + shx(P[2], 1), y0));
                y1 = fmaf(gb, shx(P[5] + shx(P[7], 1), 2), fmaf(gb, P[1] + shx(P[3], 1), y1));
                wm += 2 * WOT;
            }
            asm volatile("{\n.reg .pred p, q;\n.reg .f32 n0, s0, s1, n1;\n.reg .b16 lo, hi;\n.reg .b32 w;\n"
                         "atom.relaxed.gpu.global.add.v4.f32 {n0, s0, s1, n1}, [%0], {%4, %2, %3, %4};\n"
                         "add.f32 s0, s0, %2;\nadd.f32 s1, s1, %3;\ncvt.rn.bf16x2.f32 w, s1, s0;\nmov.b32 {lo, hi}, w;\n"
                         "setp.eq.f32 p, n0, %5;\nsetp.eq.f32 q, n1, %5;\n"
                         "@p st.global.b16 [%1], lo;\n@q st.global.b16 [%1 + 16], hi;\n"
                         "@p st.relaxed.gpu.global.v2.b32 [%0], {0, 0};\n@q st.relaxed.gpu.global.v2.b32 [%0 + 8], {0, 0};\n"
                         "setp.eq.and.u32 p, %6, 0, p;\n@p st.relaxed.gpu.global.b32 [%0 + %8], %7;\n}\n"
                         ::"l"(ap), "l"(op), "f"(y0), "f"(y1), "f"(1.f), "f"((float)(NCTA - 1)), "r"(tid),
                           "r"(tag == TAGM ? 0u : tag), "n"(offsetof(Scratch, epoch)) : "memory");
            if (tid == 0) STAMP(15);
        }
    }
}

}

extern "C" void kernel_launch(void* const* d_in, const int* in_sizes, int n_in, void* d_out, int out_size) {
    (void)in_sizes; (void)n_in; (void)out_size;
    Params p;
    p.wq[0] = (const char*)d_in[3];
    p.wq[1] = (const char*)d_in[8];
    p.x = (const char*)d_in[0];
    p.gw = (const char*)d_in[10];
    p.seg[0] = (const char*)d_in[1] + (size_t)(SK - WA) * 512;
    p.seg[1] = (const char*)d_in[2] + (size_t)(SK - WA) * 512;
    p.seg[2] = (const char*)d_in[6];
    p.seg[3] = (const char*)d_in[7];
    p.seg[4] = (const char*)d_in[4];
    p.seg[5] = (const char*)d_in[9];
    p.out = (unsigned short*)d_out;
    void* sc = nullptr;
    cudaGetSymbolAddress(&sc, g_scratch);
    p.sc = (Scratch*)(((uintptr_t)sc + 32767) & ~(uintptr_t)32767);
    cudaFuncSetAttribute(gated_mix_decode_kernel, cudaFuncAttributeMaxDynamicSharedMemorySize, SMEM_BYTES);
    gated_mix_decode_kernel<<<NCTA, NTHREADS, SMEM_BYTES>>>(p);
}
```

```cpp
#include <cuda_runtime.h>
#include <cuda.h>
#include <cuda_bf16.h>
#include <stdint.h>
#include <stddef.h>

#define NS 10
#define WIN 5
#define WINE 3
#define WMIN 1
#define RATE 652
#define RATE0 1000
#define WORATE (RATE * 7 / 8)
#define STAG 6
#define UNR 1
#define ABUF 64
#define QDELAY 500
#define OWAIT 40
#define ODELAY 200

namespace {

constexpr int DM = 448;
constexpr int SK = 8192;
constexpr int WA = 2048;
constexpr int NCTA = 128;
constexpr int UNRC = UNR;
constexpr int TILE = 16384;
constexpr int NA = 4, NB = 16;
constexpr int NKV = 2 * (NA + NB);
constexpr int NT = NKV + 4;
constexpr int WOT = 16 * DM * 2;
constexpr int NTHREADS = 320;
constexpr uint32_t SPIN_LIMIT = 1u << 18;
constexpr uint64_t EVICT_FIRST = 0x12F0000000000000ull;

constexpr int OFF_W    = 0;
constexpr int OFF_RING = 4 * WOT;
constexpr int QS = 576;
constexpr int OFF_Q    = OFF_RING + NS * TILE;
constexpr int OFF_S    = OFF_Q + 4 * QS;
constexpr int OFF_P    = OFF_S + 4096;
constexpr int OFF_M    = OFF_P + 2048;
constexpr int OFF_L    = OFF_M + 128;
constexpr int OFF_O    = OFF_L + 128;
constexpr int OFF_TAG  = OFF_O + 128;
constexpr int OFF_BAR  = OFF_TAG + 16;
constexpr int B_FULL = 0, B_ML = NT  , B_OREADY = B_ML + 2  , NBAR1 = B_OREADY + 2,
              B_EMPTY = NBAR1, NBAR = 2 * NBAR1;
constexpr int SMEM_BYTES = OFF_BAR + NBAR * 8;

constexpr uint32_t TAGM = 15u;
struct Scratch {
    float4 acc[2048];
    uint4 o[2][8][16][16][8];
    uint4 q[8][256];
    uint4 ml[2][8][16][2];
    unsigned int epoch[NCTA][8];
};
__device__ uint4 g_scratch[(sizeof(Scratch) + 32768) / 16];

struct Params {
    const char* wq[2];
    const char *x, *gw;
    Scratch* sc;
    unsigned short* out;
    const char* kv[4];
    CUtensorMap wo[2];
};

#define STAMP(i)

__device__ __forceinline__ void mbar_arrive(uint32_t bar) {
    asm volatile("mbarrier.arrive.shared::cta.b64 _, [%0];" ::"r"(bar) : "memory");
}
__device__ __forceinline__ void mbar_wait(uint32_t bar) {
    asm volatile("{\n.reg .pred p, q;\n.reg .u32 n;\nmov.u32 n, 0;\n"
                 "W:\nmbarrier.try_wait.parity.shared::cta.b64 p, [%0], 0;\nadd.u32 n, n, 1;\n"
                 "setp.lt.and.u32 q, n, %1, !p;\n@q bra W;\n}\n" ::"r"(bar), "n"(SPIN_LIMIT) : "memory");
}
__device__ __forceinline__ void ldsm4(uint32_t (&r)[4], uint32_t a) {
    asm volatile("ldmatrix.sync.aligned.m8n8.x4.shared.b16 {%0,%1,%2,%3}, [%4];"
                 : "=r"(r[0]), "=r"(r[1]), "=r"(r[2]), "=r"(r[3]) : "r"(a) : "memory");
}
__device__ __forceinline__ void ldsm4t(uint32_t (&r)[4], uint32_t a) {
    asm volatile("ldmatrix.sync.aligned.m8n8.x4.trans.shared.b16 {%0,%1,%2,%3}, [%4];"
                 : "=r"(r[0]), "=r"(r[1]), "=r"(r[2]), "=r"(r[3]) : "r"(a) : "memory");
}
__device__ __forceinline__ void mma16816(float (&c)[4], const uint32_t (&a)[4], uint32_t b0, uint32_t b1) {
    asm("mma.sync.aligned.m16n8k16.row.col.f32.bf16.bf16.f32 {%0,%1,%2,%3}, {%4,%5,%6,%7}, {%8,%9}, {%0,%1,%2,%3};"
        : "+f"(c[0]), "+f"(c[1]), "+f"(c[2]), "+f"(c[3])
        : "r"(a[0]), "r"(a[1]), "r"(a[2]), "r"(a[3]), "r"(b0), "r"(b1));
}
__device__ __forceinline__ float bf_lo(uint32_t v) { return __uint_as_float(v << 16); }
__device__ __forceinline__ float bf_hi(uint32_t v) { return __uint_as_float(v & 0xffff0000u); }
__device__ __forceinline__ uint32_t pack_bf2(float lo, float hi) {
    uint32_t r;
    asm("cvt.rn.bf16x2.f32 %0, %1, %2;" : "=r"(r) : "f"(hi), "f"(lo));
    return r;
}
__device__ __forceinline__ float round_bf(float v) { return __uint_as_float(pack_bf2(0.f, v)); }
__device__ __forceinline__ float ex2(float v) {
    float r;
    asm("ex2.approx.ftz.f32 %0, %1;" : "=f"(r) : "f"(v));
    return r;
}
__device__ __forceinline__ float rcp(float v) {
    float r;
    asm("rcp.approx.ftz.f32 %0, %1;" : "=f"(r) : "f"(v));
    return r;
}
__device__ __forceinline__ float shx(float v, int m) { return __shfl_xor_sync(0xffffffffu, v, m); }
__device__ __forceinline__ uint32_t tagged(float v, uint32_t tag) { return (__float_as_uint(v) & ~TAGM) | tag; }
__device__ __forceinline__ float untag(uint32_t v) { return __uint_as_float(v & ~TAGM); }
__device__ __forceinline__ void put2(void* p, uint32_t a, uint32_t b) {
    asm volatile("st.relaxed.gpu.global.v2.b32 [%0], {%1, %2};" ::"l"(p), "r"(a), "r"(b) : "memory");
}
template <int N>
__device__ __forceinline__ void gather(uint4 (&v)[N], const void* p, uint32_t tag) {
    uint32_t need[N];
#pragma unroll
    for (int k = 0; k < N; k++) need[k] = 1;
#pragma unroll 1
    for (uint32_t n = 0; n < SPIN_LIMIT; n++) {
#pragma unroll
        for (int k = 0; k < N; k++)
            asm volatile("{\n.reg .pred p;\nsetp.ne.u32 p, %5, 0;\n@p ld.relaxed.gpu.global.v4.b32 {%0, %1, %2, %3}, [%4];\n}\n"
                         : "+r"(v[k].x), "+r"(v[k].y), "+r"(v[k].z), "+r"(v[k].w)
                         : "l"((const char*)p + 512 * k), "r"(need[k]) : "memory");
        uint32_t any = 0;
#pragma unroll
        for (int k = 0; k < N; k++) {
            need[k] = ((v[k].x ^ tag) | (v[k].y ^ tag) | (v[k].z ^ tag) | (v[k].w ^ tag)) & TAGM;
            any |= need[k];
        }
        if (__all_sync(0xffffffffu, any == 0)) break;
    }
}

constexpr float SCALE_LOG2E = 0.0625f * 1.4426950408889634f;

__global__ void __launch_bounds__(NTHREADS, 1) gated_mix_decode_kernel(const __grid_constant__ Params p) {
    extern __shared__ __align__(1024) char smem[];
    asm volatile("prefetch.global.L2 [%0];" ::"l"(p.wq[0] + (blockIdx.x * NTHREADS + threadIdx.x) * 32));
    const uint32_t sb = (uint32_t)__cvta_generic_to_shared(smem);
    const uint32_t bars = sb + OFF_BAR;
    const uint32_t tid = threadIdx.x, lane = tid & 31;
    const uint32_t cta = blockIdx.x, head = cta >> 4, j = cta & 15;
    const uint32_t mi = lane >> 3, r = lane & 7;

    if (tid < 224) {
        const char* src = p.wq[j >> 3] + ((tid >> 3) * (16 * 8192) + head * 1024 + (j & 7) * 128 + r * 16);
        uint32_t dst = sb + OFF_W + (tid >> 3) * (16 * 128) + 16 * (r ^ (2 * mi));
#pragma unroll 1
        for (int i = 0; i < 8; i++) {
            asm volatile("cp.async.cg.shared.global.L2::cache_hint [%0], [%1], 16, %2;"
                         ::"r"(dst), "l"(src), "l"(EVICT_FIRST) : "memory");
            asm volatile("cp.async.cg.shared.global.L2::cache_hint [%0], [%1], 16, %2;"
                         ::"r"(dst ^ (128 + 16)), "l"(src + 8192), "l"(EVICT_FIRST) : "memory");
            dst += 256;
            src += 16384;
        }
    }
    uint32_t due;
    asm volatile("mov.u32 %0, %globaltimer_lo;" : "=r"(due));
    const uint32_t warp = __shfl_sync(0xffffffffu, tid >> 5, 0);
    const uint32_t g = lane >> 2, t = lane & 3;

    if (warp == 9) {
        char* const sc = (char*)p.sc;
        void* const qdst = sc + (uint32_t)(offsetof(Scratch, q) + cta * 256 + (t * 8 + g) * 8);
        put2(qdst, 0u, 0u);
        uint32_t tag;
        tag = p.sc->epoch[cta][r];
        tag = tag == 14 ? 1 : tag + 1;
        __syncwarp();
        p.sc->epoch[cta][r] = tag;
        *(uint32_t*)(smem + OFF_TAG) = tag;
        asm volatile("bar.sync 0, 320;" ::: "memory");
        {
            float q0 = 0.f, q1 = 0.f;
#pragma unroll 1
            for (int w = 0; w < 7; w++) {
                const float4 f = *(const float4*)(smem + OFF_S + (w * 32 + lane) * 16);
                q0 += f.x; q1 += f.z;
            }
            put2(qdst, pack_bf2(0.f, q0) | tag, pack_bf2(0.f, q1) | tag);
        }
        {
            float z = 0.f;
#pragma unroll 1
            for (uint32_t i = lane; i < DM / 4; i += 32) {
                const uint2 a = __ldg((const uint2*)p.x + i), b = __ldg((const uint2*)p.gw + i);
                uint32_t m0, m1;
                asm("mul.rn.bf16x2 %0, %1, %2;" : "=r"(m0) : "r"(a.x), "r"(b.x));
                asm("mul.rn.bf16x2 %0, %1, %2;" : "=r"(m1) : "r"(a.y), "r"(b.y));
                z += (bf_lo(m0) + bf_hi(m0)) + (bf_lo(m1) + bf_hi(m1));
            }
#pragma unroll 1
            for (int s = 16; s; s >>= 1) z += shx(z, s);
            const float gate = round_bf(rcp(1.f + ex2(round_bf(z) * -1.4426950408889634f)));
            *(float2*)(smem + OFF_TAG + 8) = make_float2(gate, round_bf(1.f - gate));
        }
#pragma unroll 1
        for (int br = 0; br < 2; br++) {
            mbar_wait(bars + 8 * (B_ML + br));
            float m = ((const float*)(smem + OFF_M))[br * 16 + (lane & 15)];
            float l = ((const float*)(smem + OFF_L))[br * 16 + (lane & 15)];
#pragma unroll
            for (int s = 1; s < 8; s <<= 1) { m = fmaxf(m, shx(m, s)); l += shx(l, s); }
            if (r == 0) put2(sc + (uint32_t)(offsetof(Scratch, ml) + br * 4096 + cta * 32 + lane), tagged(m, tag), tagged(l, tag));
        }
#pragma unroll 1
        for (int br = 0; br < 2; br++) {
            uint4 ml[1] = {}, v[4] = {};
            gather<1>(ml, sc + (uint32_t)(offsetof(Scratch, ml) + br * 4096 + head * 512 + (lane & 15) * 32), tag);
            const float m = untag((j & 8) ? ml[0].z : ml[0].x);
            float M = m;
#pragma unroll
            for (int s = 8; s; s >>= 1) M = fmaxf(M, shx(M, s));
            const float e = ex2((m - M) * SCALE_LOG2E);
            float L = e * untag((j & 8) ? ml[0].w : ml[0].y);
#pragma unroll
            for (int s = 8; s; s >>= 1) L += shx(L, s);
            const float wgt = e * rcp(L);
            float wk[4];
#pragma unroll
            for (int k = 0; k < 4; k++) wk[k] = __shfl_sync(0xffffffffu, wgt, 4 * k + mi);
            if (br) {
                mbar_wait(bars + 8 * (B_FULL + OWAIT));
                if (ODELAY) __nanosleep(ODELAY);
            }
            gather<4>(v, sc + (uint32_t)(offsetof(Scratch, o) + br * sizeof(Scratch::o[0]) + cta * 2048 + lane * 16), tag);
            float o0 = 0.f, o1 = 0.f, o2 = 0.f, o3 = 0.f;
#pragma unroll
            for (int k = 0; k < 4; k++) {
                o0 = fmaf(wk[k], untag(v[k].x), o0); o1 = fmaf(wk[k], untag(v[k].y), o1);
                o2 = fmaf(wk[k], untag(v[k].z), o2); o3 = fmaf(wk[k], untag(v[k].w), o3);
            }
            const bool h1 = lane & 8, h2 = lane & 16;
            const float b0 = (h1 ? o2 : o0) + shx(h1 ? o0 : o2, 8);
            const float b1 = (h1 ? o3 : o1) + shx(h1 ? o1 : o3, 8);
            const float od = (h2 ? b1 : b0) + shx(h2 ? b0 : b1, 16);
            const uint32_t d = 4 * (lane & 4) + 2 * t + ((lane >> 3) & 1) + ((lane & 16) >> 1);
            ((unsigned short*)(smem + OFF_O))[br * 32 + d] = (unsigned short)pack_bf2(od, 0.f);
            __syncwarp();
            if (lane == 0) mbar_arrive(bars + 8 * (B_OREADY + br));
            if (lane == 0) STAMP(5 + 3 * br);
        }
    } else if (warp == 8) {
        if (lane == 0) {
#pragma unroll 6
            for (int i = 0; i < NBAR1; i++) {
                asm volatile("mbarrier.init.shared::cta.b64 [%0], 1;" ::"r"(bars + 8 * i) : "memory");
                asm volatile("mbarrier.init.shared::cta.b64 [%0], 8;" ::"r"(bars + 8 * (NBAR1 + i)) : "memory");
            }
            asm volatile("fence.mbarrier_init.release.cluster;" ::: "memory");
        }
        __syncwarp();
        asm volatile("bar.arrive 0, 320;" ::: "memory");
        if (lane == 0) {
            asm volatile("prefetch.tensormap [%0];" ::"l"(&p.wo[0]) : "memory");
            asm volatile("prefetch.tensormap [%0];" ::"l"(&p.wo[1]) : "memory");
            due += RATE0 + STAG * cta;
            uint32_t i = 0;
#pragma unroll 1
            for (int s = 0; s < 5; s++) {
                const bool kv = s < 4;
                const char* src = p.kv[s & 3] + (head * (SK * 512) + j * TILE);
                const uint32_t end = i + ((s & 2) ? NB : NA);
#pragma unroll 1
                for (; i < end; i++) {
                    const uint32_t full = bars + 8 * (B_FULL + i);
                    if (kv && i >= NS) mbar_wait(full + 8 * (B_EMPTY - NS));
                    if (i >= WIN) mbar_wait(full - 8 * (kv ? WIN : WINE));
                    while (true) {
                        uint32_t now, ok;
                        asm volatile("mov.u32 %0, %globaltimer_lo;" : "=r"(now));
                        asm volatile("{\n.reg .pred p;\nmbarrier.test_wait.parity.shared::cta.b64 p, [%1], 0;\nselp.u32 %0, 1, 0, p;\n}\n"
                                     : "=r"(ok) : "r"(i >= WMIN ? full - 8 * WMIN : full) : "memory");
                        if ((int)(now - due) >= 0 || ok) break;
                    }
                    asm volatile("mbarrier.arrive.expect_tx.shared::cta.b64 _, [%0], %1;" ::"r"(full), "r"(kv ? TILE : WOT) : "memory");
                    if (kv) {
                        asm volatile("cp.async.bulk.shared::cluster.global.mbarrier::complete_tx::bytes.L2::cache_hint [%0], [%1], %2, [%3], %4;"
                                     ::"r"(sb + OFF_RING + (i % NS) * TILE), "l"(src), "n"(TILE), "r"(full), "l"(EVICT_FIRST) : "memory");
                        src += 16 * TILE;
                        due += RATE;
                    } else {
                        asm volatile("cp.async.bulk.tensor.2d.shared::cluster.global.mbarrier::complete_tx::bytes.L2::cache_hint [%0], [%1, {%2, %3}], [%4], %5;"
                                     ::"r"(sb + OFF_W + (i - NKV) * WOT), "l"(&p.wo[(i >> 1) & 1]), "r"(0),
                                       "r"((cta * 2 + (i & 1)) * (WOT / 128)), "r"(full), "l"(EVICT_FIRST) : "memory");
                        due += WORATE;
                    }
                }
            }
        }
    } else {
        char* const sc = (char*)p.sc;
        char* odst = sc + (uint32_t)(offsetof(Scratch, o) + (head * 16 + (t >> 1) * 8 + warp) * 2048 + j * 128 + ((t & 1) * 8 + g) * 8);
        put2(odst + sizeof(Scratch::o[0]), 0u, 0u);
        if (warp < 7) {
            uint32_t xb[8];
            asm volatile("ld.global.nc.v4.u32 {%0, %1, %2, %3}, [%8];\nld.global.nc.v4.u32 {%4, %5, %6, %7}, [%8 + 16];\n"
                         "cp.async.wait_all;"
                         : "=r"(xb[0]), "=r"(xb[1]), "=r"(xb[2]), "=r"(xb[3]), "=r"(xb[4]), "=r"(xb[5]), "=r"(xb[6]), "=r"(xb[7])
                         : "l"(p.x + (warp * 128 + t * 32)) : "memory");
            __syncwarp();
            const uint32_t a0 = sb + OFF_W + (warp * 64 + 16 * (r >> 1) + 2 * (mi >> 1) + (r & 1)) * 128 + 16 * ((mi & 1) ^ r);
#pragma unroll 1
            for (uint32_t i = 0; i < 4; i++) {
                float c[4] = {0.f, 0.f, 0.f, 0.f};
#pragma unroll
                for (int ks = 0; ks < 4; ks++) {
                    uint32_t a[4];
                    ldsm4t(a, (a0 ^ (32 * i)) + ks * 512);
                    mma16816(c, a, xb[2 * ks], xb[2 * ks + 1]);
                }
                if (t == i) *(float4*)(smem + OFF_S + tid * 16) = make_float4(c[0], c[1], c[2], c[3]);
            }
            asm volatile("fence.proxy.async.shared::cta;" ::: "memory");
        }
        asm volatile("bar.sync 0, 320;" ::: "memory");
        if (tid == 0) STAMP(1);
        const uint32_t tag = *(const uint32_t*)(smem + OFF_TAG);
        char* const ap = sc + ((tid >> 3) * 1024 + (tid & 4) * 64 + (tag & 1) * ABUF + t * 16);
        if (cta == 0) *(float4*)((uintptr_t)ap ^ ABUF) = make_float4(0.f, 0.f, 0.f, 0.f);

        const bool valid = t == (g & 3);
        const uint32_t lm0 = sb + OFF_RING + (8 * (mi >> 1) + r) * 512 + 16 * ((mi & 1) ^ (r >> 1));
        const uint32_t lm1 = lm0 ^ 32;
        {
            if (QDELAY) __nanosleep(QDELAY);
            uint4 v[1] = {};
            gather<1>(v, sc + (uint32_t)(offsetof(Scratch, q) + head * 4096 + tid * 16), tag);
            uint32_t* qs = (uint32_t*)(smem + OFF_Q + (warp >> 1) * QS + (warp & 1) * 256) + g * 8 + t;
            qs[0] = __byte_perm(v[0].x, v[0].z, 0x7632);
            qs[4] = __byte_perm(v[0].y, v[0].w, 0x7632);
            asm volatile("bar.sync 1, 256;" ::: "memory");
        }
        if (tid == 0) STAMP(2);
        uint32_t qa[16][4];
        {
            const uint32_t q0 = sb + OFF_Q + ((mi & 1) * 2 + (r >> 2)) * QS + 16 * ((mi >> 1) ^ (r & 3));
#pragma unroll
            for (int k = 0; k < 16; k++) ldsm4(qa[k], (q0 ^ ((k & 1) * 32)) + 64 * (k >> 1));
        }
        uint32_t T0 = 0;
#pragma unroll 1
        for (int br = 0; br < 2; br++) {
            const uint32_t nt = br ? NB : NA;
            float mx = -INFINITY;
#pragma unroll 1
            for (uint32_t kt = warp >> 1; kt < nt; kt += 4) {
                const uint32_t T = T0 + kt, off = (T % NS) * TILE + (warp & 1) * 8192;
                mbar_wait(bars + 8 * (B_FULL + T));
                float c0[4] = {0.f, 0.f, 0.f, 0.f}, c1[4] = {0.f, 0.f, 0.f, 0.f};
#pragma unroll
                for (int k = 0; k < 16; k++) {
                    uint32_t b[4];
                    ldsm4(b, ((k & 1) ? lm1 : lm0) + off + 64 * (k >> 1));
                    mma16816(c0, qa[k], b[0], b[1]);
                    mma16816(c1, qa[k], b[2], b[3]);
                }
                __syncwarp();
                if (lane == 0) asm volatile("mbarrier.arrive.shared::cta.b64 _, [%0], 4;" ::"r"(bars + 8 * (B_EMPTY + T)) : "memory");
                float4 s;
                s.x = round_bf(br ? c0[2] : c0[0]); s.y = round_bf(br ? c0[3] : c0[1]);
                s.z = round_bf(br ? c1[2] : c1[0]); s.w = round_bf(br ? c1[3] : c1[1]);
                if (valid) *(float4*)(smem + OFF_S + ((2 * kt + (warp & 1)) * 8 + g) * 16) = s;
                mx = fmaxf(fmaxf(mx, fmaxf(s.x, s.y)), fmaxf(s.z, s.w));
            }
            mx = fmaxf(mx, shx(mx, 5));
            mx = fmaxf(mx, shx(mx, 10));
            float* mred = (float*)(smem + OFF_M) + br * 16;
            if ((lane & 15) == 0) mred[(lane >> 1) + warp] = mx;
            asm volatile("bar.sync 1, 256;" ::: "memory");
            if (tid == 0) STAMP(3 + 3 * br);
            {
                const float4 m0 = *(const float4*)(mred + (lane & 4) * 2), m1 = *(const float4*)(mred + (lane & 4) * 2 + 4);
                const float M = fmaxf(fmaxf(fmaxf(m0.x, m0.y), fmaxf(m0.z, m0.w)), fmaxf(fmaxf(m1.x, m1.y), fmaxf(m1.z, m1.w)));
                const float4 s = *(const float4*)(smem + OFF_S + tid * 16);
                const uint32_t p0 = pack_bf2(ex2((s.x - M) * SCALE_LOG2E), ex2((s.y - M) * SCALE_LOG2E));
                const uint32_t p1 = pack_bf2(ex2((s.z - M) * SCALE_LOG2E), ex2((s.w - M) * SCALE_LOG2E));
                *(uint2*)(smem + OFF_P + ((tid >> 4) * 8 + r) * 16 + (tid & 8)) = make_uint2(p0, p1);
                float l = (bf_lo(p0) + bf_hi(p0)) + (bf_lo(p1) + bf_hi(p1));
                l += shx(l, 1); l += shx(l, 2); l += shx(l, 8); l += shx(l, 16);
                if ((lane & ~4) == 0) mred[(OFF_L - OFF_M) / 4 + lane * 2 + warp] = tid < nt * 16 ? l : 0.f;
            }
            asm volatile("bar.sync 1, 256;" ::: "memory");
            if (tid == 0) mbar_arrive(bars + 8 * (B_ML + br));
            T0 += nt;
            float o0[4] = {0.f, 0.f, 0.f, 0.f}, o1[4] = {0.f, 0.f, 0.f, 0.f};
#pragma unroll 1
            for (uint32_t vt = 0; vt < nt; vt++) {
                const uint32_t T = T0 + vt, off = (T % NS) * TILE + warp * 64;
                uint4 pb = make_uint4(0u, 0u, 0u, 0u);
                if (valid) pb = *(const uint4*)(smem + OFF_P + (vt * 8 + g) * 16);
                mbar_wait(bars + 8 * (B_FULL + T));
                uint32_t a[4][4];
                ldsm4t(a[0], lm0 + off);
                ldsm4t(a[1], lm1 + off);
                ldsm4t(a[2], lm0 + off + 8192);
                ldsm4t(a[3], lm1 + off + 8192);
                mma16816(o0, a[0], pb.x, pb.y);
                mma16816(o1, a[1], pb.x, pb.y);
                mma16816(o0, a[2], pb.z, pb.w);
                mma16816(o1, a[3], pb.z, pb.w);
                __syncwarp();
                if (lane == 0) mbar_arrive(bars + 8 * (B_EMPTY + T));
            }
            T0 += nt;
            if (tid == 0) STAMP(4 + 3 * br);
            const float u0 = o0[0] + o0[3] + shx(o1[0] + o1[3], 1);
            const float u1 = o0[2] + o0[1] + shx(o1[2] + o1[1], 1);
            put2(odst, tagged(u0, tag), tagged(u1, tag));
            odst += sizeof(Scratch::o[0]);
        }
        if (warp < 7) {
            uint32_t wm = sb + OFF_W + (8 * (mi >> 1) + r) * (DM * 2) + 128 * warp + 16 * ((mi & 1) ^ ((warp - r) & 7));
            unsigned short* op = p.out + (64 * warp + 16 * t + g);
            float y0 = 0.f, y1 = 0.f;
#pragma unroll UNRC
            for (int br = 0; br < 2; br++) {
                mbar_wait(bars + 8 * (B_OREADY + br));
                const float gb = *(const float*)(smem + OFF_TAG + 8 + 4 * br);
                uint32_t ob[4], a[2][4][4];
#pragma unroll
                for (int i = 0; i < 4; i++) ob[i] = ((const uint32_t*)(smem + OFF_O))[br * 16 + 4 * i + t];
#pragma unroll
                for (int x = 0; x < 2; x++) {
                    mbar_wait(bars + 8 * (B_FULL + NKV + 2 * br + x));
#pragma unroll
                    for (int i = 0; i < 4; i++) ldsm4t(a[x][i], (wm ^ (32 * i)) + x * WOT);
                }
                float c[4][4] = {};
#pragma unroll
                for (int i = 0; i < 4; i++) {
                    mma16816(c[i], a[0][i], ob[0], ob[1]);
                    mma16816(c[i], a[1][i], ob[2], ob[3]);
                }
                y0 = fmaf(gb, (t & 2) ? ((t & 1) ? c[3][0] : c[2][0]) : ((t & 1) ? c[1][0] : c[0][0]), y0);
                y1 = fmaf(gb, (t & 2) ? ((t & 1) ? c[3][2] : c[2][2]) : ((t & 1) ? c[1][2] : c[0][2]), y1);
                wm += 2 * WOT;
                asm volatile("{\n.reg .pred l, p, q;\n.reg .f32 n0, s0, s1, n1;\n.reg .b16 lo, hi;\n.reg .b32 w;\n"
                             "setp.ne.u32 l, %6, 0;\nmov.f32 n0, %4;\nmov.f32 n1, %4;\nmov.f32 s0, %4;\nmov.f32 s1, %4;\n"
                             "@l atom.relaxed.gpu.global.add.v4.f32 {n0, s0, s1, n1}, [%0], {%4, %2, %3, %4};\n"
                             "add.f32 s0, s0, %2;\nadd.f32 s1, s1, %3;\ncvt.rn.bf16x2.f32 w, s1, s0;\nmov.b32 {lo, hi}, w;\n"
                             "setp.eq.f32 p, n0, %5;\nsetp.eq.f32 q, n1, %5;\n"
                             "@p st.global.b16 [%1], lo;\n@q st.global.b16 [%1 + 16], hi;\n}\n"
                             ::"l"(ap), "l"(op), "f"(y0), "f"(y1), "f"(1.f), "f"((float)(NCTA - 1)), "r"(br) : "memory");
            }
            if (tid == 0) STAMP(15);
        }
    }
}

}

extern "C" void kernel_launch(void* const* d_in, const int* in_sizes, int n_in, void* d_out, int out_size) {
    (void)in_sizes; (void)n_in; (void)out_size;
    Params p;
    p.wq[0] = (const char*)d_in[3];
    p.wq[1] = (const char*)d_in[8];
    p.x = (const char*)d_in[0];
    p.gw = (const char*)d_in[10];
    p.kv[0] = (const char*)d_in[1] + (size_t)(SK - WA) * 512;
    p.kv[1] = (const char*)d_in[2] + (size_t)(SK - WA) * 512;
    p.kv[2] = (const char*)d_in[6];
    p.kv[3] = (const char*)d_in[7];
    p.out = (unsigned short*)d_out;
    void* sc = nullptr;
    cudaGetSymbolAddress(&sc, g_scratch);
    p.sc = (Scratch*)(((uintptr_t)sc + 32767) & ~(uintptr_t)32767);
    typedef CUresult (*EncodeFn)(CUtensorMap*, CUtensorMapDataType, cuuint32_t, void*, const cuuint64_t*, const cuuint64_t*,
                                 const cuuint32_t*, const cuuint32_t*, CUtensorMapInterleave, CUtensorMapSwizzle,
                                 CUtensorMapL2promotion, CUtensorMapFloatOOBfill);
    void* fn = nullptr;
    cudaDriverEntryPointQueryResult qr;
    cudaGetDriverEntryPoint("cuTensorMapEncodeTiled", &fn, cudaEnableDefault, &qr);
    for (int b = 0; b < 2; b++) {
        const cuuint64_t dims[2] = {64, 4096 * 7}, strides[1] = {128};
        const cuuint32_t box[2] = {64, WOT / 128}, es[2] = {1, 1};
        ((EncodeFn)fn)(&p.wo[b], CU_TENSOR_MAP_DATA_TYPE_BFLOAT16, 2, d_in[b ? 9 : 4], dims, strides, box, es,
                       CU_TENSOR_MAP_INTERLEAVE_NONE, CU_TENSOR_MAP_SWIZZLE_128B, CU_TENSOR_MAP_L2_PROMOTION_NONE,
                       CU_TENSOR_MAP_FLOAT_OOB_FILL_NONE);
    }
    cudaFuncSetAttribute(gated_mix_decode_kernel, cudaFuncAttributeMaxDynamicSharedMemorySize, SMEM_BYTES);
    gated_mix_decode_kernel<<<NCTA, NTHREADS, SMEM_BYTES>>>(p);
}
```

```cpp
#include <cuda_runtime.h>
#include <cuda.h>
#include <cuda_bf16.h>
#include <stdint.h>
#include <stddef.h>

namespace {

constexpr int DM = 448;
constexpr int SK = 8192;
constexpr int WA = 2048;
constexpr int NCTA = 128;
constexpr int TILE = 16384;
constexpr int NA = 4, NB = 16;
constexpr int NKV = 2 * (NA + NB);
constexpr int NT = NKV + 4;
constexpr int WOT = 16 * DM * 2;
constexpr int NTHREADS = 320;
constexpr int NS = 10;
constexpr int RATE0 = 970;
constexpr int RATE = 652;
constexpr int WORATE = RATE * 7 / 8;
constexpr int STAG = 6;
constexpr int WIN = 5, WINE = 3;
constexpr int WMIN = 1;
constexpr int QWAIT = 3, OWAIT = NKV + 1;
constexpr uint32_t SPIN_LIMIT = 1u << 18;

constexpr int OFF_W    = 0;
constexpr int OFF_RING = 4 * WOT;
constexpr int QS = 576;
constexpr int OFF_Q    = OFF_RING + NS * TILE;
constexpr int OFF_S    = OFF_Q + 4 * QS;
constexpr int OFF_P    = OFF_S + 4096;
constexpr int OFF_M    = OFF_P + 2048;
constexpr int OFF_L    = OFF_M + 128;
constexpr int OFF_O    = OFF_L + 128;
constexpr int OFF_TAG  = OFF_O + 128;
constexpr int OFF_BAR  = OFF_TAG + 16;
constexpr int B_FULL = 0, B_ML = NT  , B_OREADY = B_ML + 2  , NBAR1 = B_OREADY + 2,
              B_EMPTY = NBAR1, NBAR = 2 * NBAR1;
constexpr int SMEM_BYTES = OFF_BAR + NBAR * 8;

constexpr uint32_t TAGM = 15u;
struct Scratch {
    float4 acc[2048];
    uint4 o[2][8][16][16][8];
    uint4 q[8][256];
    uint4 ml[2][8][16][2];
    unsigned int epoch[NCTA][32];
};
__device__ uint4 g_scratch[(sizeof(Scratch) + 32768) / 16];

struct Params {
    const char* wq[2];
    const char *x, *gw;
    Scratch* sc;
    unsigned short* out;
    const char* kv[4];
    CUtensorMap wo[2];
};

__device__ __forceinline__ void mbar_arrive(uint32_t bar) {
    asm volatile("mbarrier.arrive.shared::cta.b64 _, [%0];" ::"r"(bar) : "memory");
}
__device__ __forceinline__ void mbar_wait(uint32_t bar) {
    asm volatile("{\n.reg .pred p, q;\n.reg .u32 n;\nmov.u32 n, 0;\n"
                 "W:\nmbarrier.try_wait.parity.shared::cta.b64 p, [%0], 0;\nadd.u32 n, n, 1;\n"
                 "setp.lt.and.u32 q, n, %1, !p;\n@q bra W;\n}\n" ::"r"(bar), "n"(SPIN_LIMIT) : "memory");
}
__device__ __forceinline__ void ldsm4(uint32_t (&r)[4], uint32_t a) {
    asm volatile("ldmatrix.sync.aligned.m8n8.x4.shared.b16 {%0,%1,%2,%3}, [%4];"
                 : "=r"(r[0]), "=r"(r[1]), "=r"(r[2]), "=r"(r[3]) : "r"(a) : "memory");
}
__device__ __forceinline__ void ldsm4t(uint32_t (&r)[4], uint32_t a) {
    asm volatile("ldmatrix.sync.aligned.m8n8.x4.trans.shared.b16 {%0,%1,%2,%3}, [%4];"
                 : "=r"(r[0]), "=r"(r[1]), "=r"(r[2]), "=r"(r[3]) : "r"(a) : "memory");
}
__device__ __forceinline__ void mma16816(float (&c)[4], const uint32_t (&a)[4], uint32_t b0, uint32_t b1) {
    asm("mma.sync.aligned.m16n8k16.row.col.f32.bf16.bf16.f32 {%0,%1,%2,%3}, {%4,%5,%6,%7}, {%8,%9}, {%0,%1,%2,%3};"
        : "+f"(c[0]), "+f"(c[1]), "+f"(c[2]), "+f"(c[3])
        : "r"(a[0]), "r"(a[1]), "r"(a[2]), "r"(a[3]), "r"(b0), "r"(b1));
}
__device__ __forceinline__ float bf_lo(uint32_t v) { return __uint_as_float(v << 16); }
__device__ __forceinline__ float bf_hi(uint32_t v) { return __uint_as_float(v & 0xffff0000u); }
__device__ __forceinline__ uint32_t pack_bf2(float lo, float hi) {
    uint32_t r;
    asm("cvt.rn.bf16x2.f32 %0, %1, %2;" : "=r"(r) : "f"(hi), "f"(lo));
    return r;
}
__device__ __forceinline__ float round_bf(float v) { return __uint_as_float(pack_bf2(0.f, v)); }
__device__ __forceinline__ float ex2(float v) {
    float r;
    asm("ex2.approx.ftz.f32 %0, %1;" : "=f"(r) : "f"(v));
    return r;
}
__device__ __forceinline__ float rcp(float v) {
    float r;
    asm("rcp.approx.ftz.f32 %0, %1;" : "=f"(r) : "f"(v));
    return r;
}
__device__ __forceinline__ float shx(float v, int m) { return __shfl_xor_sync(0xffffffffu, v, m); }
__device__ __forceinline__ uint32_t tagged(float v, uint32_t tag) { return (__float_as_uint(v) & ~TAGM) | tag; }
__device__ __forceinline__ float untag(uint32_t v) { return __uint_as_float(v & ~TAGM); }
__device__ __forceinline__ void put2(void* p, uint32_t a, uint32_t b) {
    asm volatile("st.relaxed.gpu.global.v2.b32 [%0], {%1, %2};" ::"l"(p), "r"(a), "r"(b) : "memory");
}
template <int N>
__device__ __forceinline__ void gather(uint4 (&v)[N], const void* p, uint32_t tag) {
    uint32_t n = 0, bad;
    do {
        bad = 0;
#pragma unroll
        for (int k = 0; k < N; k++)
            asm volatile("ld.relaxed.gpu.global.v4.b32 {%0, %1, %2, %3}, [%4];"
                         : "=r"(v[k].x), "=r"(v[k].y), "=r"(v[k].z), "=r"(v[k].w) : "l"((const char*)p + 512 * k) : "memory");
#pragma unroll
        for (int k = 0; k < N; k++) bad |= (v[k].x ^ tag) | (v[k].y ^ tag) | (v[k].z ^ tag) | (v[k].w ^ tag);
    } while (__any_sync(0xffffffffu, bad & TAGM) && ++n < SPIN_LIMIT);
}
__device__ __forceinline__ uint64_t evict_first() {
    uint64_t pol;
    asm volatile("createpolicy.fractional.L2::evict_first.b64 %0, 1.0;" : "=l"(pol));
    return pol;
}

constexpr float SCALE_LOG2E = 0.0625f * 1.4426950408889634f;

__global__ void __launch_bounds__(NTHREADS, 1) gated_mix_decode_kernel(const __grid_constant__ Params p) {
    extern __shared__ __align__(1024) char smem[];
    asm volatile("prefetch.global.L2 [%0];" ::"l"(p.wq[0] + (blockIdx.x * NTHREADS + threadIdx.x) * 32));
    const uint32_t sb = (uint32_t)__cvta_generic_to_shared(smem);
    const uint32_t bars = sb + OFF_BAR;
    const uint32_t tid = threadIdx.x, lane = tid & 31;
    const uint32_t cta = blockIdx.x, head = cta >> 4, j = cta & 15;
    const uint32_t mi = lane >> 3, r = lane & 7;

    if (tid < 224) {
        const uint64_t pol = evict_first();
        const char* src = p.wq[j >> 3] + ((tid >> 3) * (16 * 8192) + head * 1024 + (j & 7) * 128 + r * 16);
        uint32_t dst = sb + OFF_W + (tid >> 3) * (16 * 128) + 16 * (r ^ (2 * mi));
#pragma unroll 1
        for (int i = 0; i < 8; i++) {
            asm volatile("cp.async.cg.shared.global.L2::cache_hint [%0], [%1], 16, %2;"
                         ::"r"(dst), "l"(src), "l"(pol) : "memory");
            asm volatile("cp.async.cg.shared.global.L2::cache_hint [%0], [%1], 16, %2;"
                         ::"r"(dst ^ (128 + 16)), "l"(src + 8192), "l"(pol) : "memory");
            dst += 256;
            src += 16384;
        }
    }
    uint32_t due;
    asm volatile("mov.u32 %0, %globaltimer_lo;" : "=r"(due));
    const uint32_t warp = __shfl_sync(0xffffffffu, tid >> 5, 0);
    const uint32_t g = lane >> 2, t = lane & 3;

    if (warp == 9) {
        char* const sc = (char*)p.sc;
        void* const qdst = sc + (uint32_t)(offsetof(Scratch, q) + cta * 256 + (t * 8 + g) * 8);
        uint32_t tag = p.sc->epoch[cta][0];
        tag = tag == 14 ? 1 : tag + 1;
        __syncwarp();
        p.sc->epoch[cta][0] = tag;
        *(uint32_t*)(smem + OFF_TAG) = tag;
        asm volatile("bar.sync 2, 320;" ::: "memory");
        {
            float q0 = 0.f, q1 = 0.f;
#pragma unroll 1
            for (int w = 0; w < 7; w++) {
                const float4 f = *(const float4*)(smem + OFF_S + (w * 32 + lane) * 16);
                q0 += f.x; q1 += f.z;
            }
            put2(qdst, pack_bf2(0.f, q0) | tag, pack_bf2(0.f, q1) | tag);
        }
        {
            float z = 0.f;
#pragma unroll 1
            for (uint32_t i = lane; i < DM / 4; i += 32) {
                const uint2 a = __ldg((const uint2*)p.x + i), b = __ldg((const uint2*)p.gw + i);
                uint32_t m0, m1;
                asm("mul.rn.bf16x2 %0, %1, %2;" : "=r"(m0) : "r"(a.x), "r"(b.x));
                asm("mul.rn.bf16x2 %0, %1, %2;" : "=r"(m1) : "r"(a.y), "r"(b.y));
                z += (bf_lo(m0) + bf_hi(m0)) + (bf_lo(m1) + bf_hi(m1));
            }
#pragma unroll 1
            for (int s = 16; s; s >>= 1) z += shx(z, s);
            const float gate = round_bf(rcp(1.f + ex2(round_bf(z) * -1.4426950408889634f)));
            *(float2*)(smem + OFF_TAG + 8) = make_float2(gate, round_bf(1.f - gate));
        }
#pragma unroll 1
        for (int br = 0; br < 2; br++) {
            mbar_wait(bars + 8 * (B_ML + br));
            float m = ((const float*)(smem + OFF_M))[br * 16 + (lane & 15)];
            float l = ((const float*)(smem + OFF_L))[br * 16 + (lane & 15)];
#pragma unroll
            for (int s = 1; s < 8; s <<= 1) { m = fmaxf(m, shx(m, s)); l += shx(l, s); }
            if (r == 0) put2(sc + (uint32_t)(offsetof(Scratch, ml) + br * 4096 + cta * 32 + lane), tagged(m, tag), tagged(l, tag));
        }
#pragma unroll 1
        for (int br = 0; br < 2; br++) {
            uint4 ml[1], v[4];
            gather<1>(ml, sc + (uint32_t)(offsetof(Scratch, ml) + br * 4096 + head * 512 + (lane & 15) * 32), tag);
            const float m = untag((j & 8) ? ml[0].z : ml[0].x);
            float M = m;
#pragma unroll
            for (int s = 8; s; s >>= 1) M = fmaxf(M, shx(M, s));
            const float e = ex2((m - M) * SCALE_LOG2E);
            float L = e * untag((j & 8) ? ml[0].w : ml[0].y);
#pragma unroll
            for (int s = 8; s; s >>= 1) L += shx(L, s);
            const float wgt = e * rcp(L);
            float wk[4];
#pragma unroll
            for (int k = 0; k < 4; k++) wk[k] = __shfl_sync(0xffffffffu, wgt, 4 * k + mi);
            if (br) mbar_wait(bars + 8 * (B_FULL + OWAIT));
            gather<4>(v, sc + (uint32_t)(offsetof(Scratch, o) + br * sizeof(Scratch::o[0]) + cta * 2048 + lane * 16), tag);
            float o0 = 0.f, o1 = 0.f, o2 = 0.f, o3 = 0.f;
#pragma unroll
            for (int k = 0; k < 4; k++) {
                o0 = fmaf(wk[k], untag(v[k].x), o0); o1 = fmaf(wk[k], untag(v[k].y), o1);
                o2 = fmaf(wk[k], untag(v[k].z), o2); o3 = fmaf(wk[k], untag(v[k].w), o3);
            }
            const bool h1 = lane & 8, h2 = lane & 16;
            const float b0 = (h1 ? o2 : o0) + shx(h1 ? o0 : o2, 8);
            const float b1 = (h1 ? o3 : o1) + shx(h1 ? o1 : o3, 8);
            const float od = (h2 ? b1 : b0) + shx(h2 ? b0 : b1, 16);
            const uint32_t d = 4 * (lane & 4) + 2 * t + ((lane >> 3) & 1) + ((lane & 16) >> 1);
            ((unsigned short*)(smem + OFF_O))[br * 32 + d] = (unsigned short)pack_bf2(od, 0.f);
            __syncwarp();
            if (lane == 0) mbar_arrive(bars + 8 * (B_OREADY + br));
        }
    } else if (warp == 8) {
        if (lane == 0) {
#pragma unroll 6
            for (int i = 0; i < NBAR1; i++) {
                asm volatile("mbarrier.init.shared::cta.b64 [%0], 1;" ::"r"(bars + 8 * i) : "memory");
                asm volatile("mbarrier.init.shared::cta.b64 [%0], 8;" ::"r"(bars + 8 * (NBAR1 + i)) : "memory");
            }
            asm volatile("fence.mbarrier_init.release.cluster;" ::: "memory");
        }
        __syncwarp();
        asm volatile("bar.arrive 2, 320;" ::: "memory");
        if (lane == 0) {
            asm volatile("prefetch.tensormap [%0];" ::"l"(&p.wo[0]) : "memory");
            asm volatile("prefetch.tensormap [%0];" ::"l"(&p.wo[1]) : "memory");
            const uint64_t pol = evict_first();
            due += RATE0 + STAG * cta;
            uint32_t i = 0;
#pragma unroll 1
            for (int s = 0; s < 5; s++) {
                const bool kv = s < 4;
                const char* src = p.kv[s & 3] + (head * (SK * 512) + j * TILE);
                const uint32_t end = i + ((s & 2) ? NB : NA);
#pragma unroll 1
                for (; i < end; i++) {
                    const uint32_t full = bars + 8 * (B_FULL + i);
                    if (kv && i >= NS) mbar_wait(full + 8 * (B_EMPTY - NS));
                    if (i >= WIN) mbar_wait(full - 8 * (kv ? WIN : WINE));
                    while (true) {
                        uint32_t now, ok;
                        asm volatile("mov.u32 %0, %globaltimer_lo;" : "=r"(now));
                        asm volatile("{\n.reg .pred p;\nmbarrier.test_wait.parity.shared::cta.b64 p, [%1], 0;\nselp.u32 %0, 1, 0, p;\n}\n"
                                     : "=r"(ok) : "r"(i >= WMIN ? full - 8 * WMIN : full) : "memory");
                        if ((int)(now - due) >= 0 || ok) break;
                    }
                    asm volatile("mbarrier.arrive.expect_tx.shared::cta.b64 _, [%0], %1;" ::"r"(full), "r"(kv ? TILE : WOT) : "memory");
                    if (kv) {
                        asm volatile("cp.async.bulk.shared::cluster.global.mbarrier::complete_tx::bytes.L2::cache_hint [%0], [%1], %2, [%3], %4;"
                                     ::"r"(sb + OFF_RING + (i % NS) * TILE), "l"(src), "n"(TILE), "r"(full), "l"(pol) : "memory");
                        src += 16 * TILE;
                        due += RATE;
                    } else {
                        asm volatile("cp.async.bulk.tensor.2d.shared::cluster.global.mbarrier::complete_tx::bytes.L2::cache_hint [%0], [%1, {%2, %3}], [%4], %5;"
                                     ::"r"(sb + OFF_W + (i - NKV) * WOT), "l"(&p.wo[(i >> 1) & 1]), "r"(0),
                                       "r"((cta * 2 + (i & 1)) * (WOT / 128)), "r"(full), "l"(pol) : "memory");
                        due += WORATE;
                    }
                }
            }
        }
    } else {
        char* const sc = (char*)p.sc;
        char* odst = sc + (uint32_t)(offsetof(Scratch, o) + (head * 16 + (t >> 1) * 8 + warp) * 2048 + j * 128 + ((t & 1) * 8 + g) * 8);
        if (warp < 7) {
            uint32_t xb[8];
            asm volatile("ld.global.nc.v4.u32 {%0, %1, %2, %3}, [%8];\nld.global.nc.v4.u32 {%4, %5, %6, %7}, [%8 + 16];\n"
                         "cp.async.wait_all;"
                         : "=r"(xb[0]), "=r"(xb[1]), "=r"(xb[2]), "=r"(xb[3]), "=r"(xb[4]), "=r"(xb[5]), "=r"(xb[6]), "=r"(xb[7])
                         : "l"(p.x + (warp * 128 + t * 32)) : "memory");
            __syncwarp();
            const uint32_t a0 = sb + OFF_W + (warp * 64 + 16 * (r >> 1) + 2 * (mi >> 1) + (r & 1)) * 128 + 16 * ((mi & 1) ^ r);
#pragma unroll 1
            for (uint32_t i = 0; i < 4; i++) {
                float c[4] = {0.f, 0.f, 0.f, 0.f};
#pragma unroll
                for (int ks = 0; ks < 4; ks++) {
                    uint32_t a[4];
                    ldsm4t(a, (a0 ^ (32 * i)) + ks * 512);
                    mma16816(c, a, xb[2 * ks], xb[2 * ks + 1]);
                }
                if (t == i) *(float4*)(smem + OFF_S + tid * 16) = make_float4(c[0], c[1], c[2], c[3]);
            }
            asm volatile("fence.proxy.async.shared::cta;" ::: "memory");
        }
        asm volatile("bar.sync 2, 320;" ::: "memory");
        const uint32_t tag = *(const uint32_t*)(smem + OFF_TAG);
        char* const ap = sc + ((tid >> 3) * 1024 + (tid & 4) * 64 + (tag & 1) * 64 + t * 16);
        if (cta == 0) *(float4*)((uintptr_t)ap ^ 64) = make_float4(0.f, 0.f, 0.f, 0.f);

        const bool valid = t == (g & 3);
        const uint32_t lm0 = sb + OFF_RING + (8 * (mi >> 1) + r) * 512 + 16 * ((mi & 1) ^ (r >> 1));
        const uint32_t lm1 = lm0 ^ 32;
        {
            mbar_wait(bars + 8 * (B_FULL + QWAIT));
            uint4 v[1];
            gather<1>(v, sc + (uint32_t)(offsetof(Scratch, q) + head * 4096 + tid * 16), tag);
            uint32_t* qs = (uint32_t*)(smem + OFF_Q + (warp >> 1) * QS + (warp & 1) * 256) + g * 8 + t;
            qs[0] = __byte_perm(v[0].x, v[0].z, 0x7632);
            qs[4] = __byte_perm(v[0].y, v[0].w, 0x7632);
            asm volatile("bar.sync 1, 256;" ::: "memory");
        }
        uint32_t qa[16][4];
        {
            const uint32_t q0 = sb + OFF_Q + ((mi & 1) * 2 + (r >> 2)) * QS + 16 * ((mi >> 1) ^ (r & 3));
#pragma unroll
            for (int k = 0; k < 16; k++) ldsm4(qa[k], (q0 ^ ((k & 1) * 32)) + 64 * (k >> 1));
        }
        uint32_t T0 = 0;
#pragma unroll 1
        for (int br = 0; br < 2; br++) {
            const uint32_t nt = br ? NB : NA;
            float mx = -INFINITY;
#pragma unroll 1
            for (uint32_t kt = warp >> 1; kt < nt; kt += 4) {
                const uint32_t T = T0 + kt, off = (T % NS) * TILE + (warp & 1) * 8192;
                mbar_wait(bars + 8 * (B_FULL + T));
                float c0[4] = {0.f, 0.f, 0.f, 0.f}, c1[4] = {0.f, 0.f, 0.f, 0.f};
#pragma unroll
                for (int k = 0; k < 16; k++) {
                    uint32_t b[4];
                    ldsm4(b, ((k & 1) ? lm1 : lm0) + off + 64 * (k >> 1));
                    mma16816(c0, qa[k], b[0], b[1]);
                    mma16816(c1, qa[k], b[2], b[3]);
                }
                __syncwarp();
                if (lane == 0) asm volatile("mbarrier.arrive.shared::cta.b64 _, [%0], 4;" ::"r"(bars + 8 * (B_EMPTY + T)) : "memory");
                float4 s;
                s.x = round_bf(br ? c0[2] : c0[0]); s.y = round_bf(br ? c0[3] : c0[1]);
                s.z = round_bf(br ? c1[2] : c1[0]); s.w = round_bf(br ? c1[3] : c1[1]);
                if (valid) *(float4*)(smem + OFF_S + ((2 * kt + (warp & 1)) * 8 + g) * 16) = s;
                mx = fmaxf(fmaxf(mx, fmaxf(s.x, s.y)), fmaxf(s.z, s.w));
            }
            mx = fmaxf(mx, shx(mx, 5));
            mx = fmaxf(mx, shx(mx, 10));
            float* mred = (float*)(smem + OFF_M) + br * 16;
            if ((lane & 15) == 0) mred[(lane >> 1) + warp] = mx;
            asm volatile("bar.sync 1, 256;" ::: "memory");
            {
                const float4 m0 = *(const float4*)(mred + (lane & 4) * 2), m1 = *(const float4*)(mred + (lane & 4) * 2 + 4);
                const float M = fmaxf(fmaxf(fmaxf(m0.x, m0.y), fmaxf(m0.z, m0.w)), fmaxf(fmaxf(m1.x, m1.y), fmaxf(m1.z, m1.w)));
                const float4 s = *(const float4*)(smem + OFF_S + tid * 16);
                const uint32_t p0 = pack_bf2(ex2((s.x - M) * SCALE_LOG2E), ex2((s.y - M) * SCALE_LOG2E));
                const uint32_t p1 = pack_bf2(ex2((s.z - M) * SCALE_LOG2E), ex2((s.w - M) * SCALE_LOG2E));
                *(uint2*)(smem + OFF_P + ((tid >> 4) * 8 + r) * 16 + (tid & 8)) = make_uint2(p0, p1);
                float l = (bf_lo(p0) + bf_hi(p0)) + (bf_lo(p1) + bf_hi(p1));
                l += shx(l, 1); l += shx(l, 2); l += shx(l, 8); l += shx(l, 16);
                if ((lane & ~4) == 0) mred[(OFF_L - OFF_M) / 4 + lane * 2 + warp] = tid < nt * 16 ? l : 0.f;
            }
            asm volatile("bar.sync 1, 256;" ::: "memory");
            if (tid == 0) mbar_arrive(bars + 8 * (B_ML + br));
            T0 += nt;
            float o0[4] = {0.f, 0.f, 0.f, 0.f}, o1[4] = {0.f, 0.f, 0.f, 0.f};
#pragma unroll 1
            for (uint32_t vt = 0; vt < nt; vt++) {
                const uint32_t T = T0 + vt, off = (T % NS) * TILE + warp * 64;
                uint4 pb = make_uint4(0u, 0u, 0u, 0u);
                if (valid) pb = *(const uint4*)(smem + OFF_P + (vt * 8 + g) * 16);
                mbar_wait(bars + 8 * (B_FULL + T));
                uint32_t a[4][4];
                ldsm4t(a[0], lm0 + off);
                ldsm4t(a[1], lm1 + off);
                ldsm4t(a[2], lm0 + off + 8192);
                ldsm4t(a[3], lm1 + off + 8192);
                mma16816(o0, a[0], pb.x, pb.y);
                mma16816(o1, a[1], pb.x, pb.y);
                mma16816(o0, a[2], pb.z, pb.w);
                mma16816(o1, a[3], pb.z, pb.w);
                __syncwarp();
                if (lane == 0) mbar_arrive(bars + 8 * (B_EMPTY + T));
            }
            T0 += nt;
            const float u0 = o0[0] + o0[3] + shx(o1[0] + o1[3], 1);
            const float u1 = o0[2] + o0[1] + shx(o1[2] + o1[1], 1);
            put2(odst, tagged(u0, tag), tagged(u1, tag));
            odst += sizeof(Scratch::o[0]);
        }
        if (warp < 7) {
            uint32_t wm = sb + OFF_W + (8 * (mi >> 1) + r) * (DM * 2) + 128 * warp + 16 * ((mi & 1) ^ ((warp - r) & 7));
            unsigned short* op = p.out + (64 * warp + 16 * t + g);
            float y0 = 0.f, y1 = 0.f;
#pragma unroll 1
            for (int br = 0; br < 2; br++) {
                uint32_t ob[4], a[4][4];
                float c[4][4] = {};
                mbar_wait(bars + 8 * (B_FULL + NKV + 2 * br));
#pragma unroll
                for (int i = 0; i < 4; i++) ldsm4t(a[i], wm ^ (32 * i));
                mbar_wait(bars + 8 * (B_OREADY + br));
                const float gb = *(const float*)(smem + OFF_TAG + 8 + 4 * br);
#pragma unroll
                for (int i = 0; i < 4; i++) ob[i] = ((const uint32_t*)(smem + OFF_O))[br * 16 + 4 * i + t];
#pragma unroll
                for (int i = 0; i < 4; i++) mma16816(c[i], a[i], ob[0], ob[1]);
                asm volatile("" : "+f"(c[0][0]), "+f"(c[1][0]), "+f"(c[2][0]), "+f"(c[3][0]));
                mbar_wait(bars + 8 * (B_FULL + NKV + 2 * br + 1));
#pragma unroll
                for (int i = 0; i < 4; i++) ldsm4t(a[i], (wm ^ (32 * i)) + WOT);
#pragma unroll
                for (int i = 0; i < 4; i++) mma16816(c[i], a[i], ob[2], ob[3]);
                y0 = fmaf(gb, (t & 2) ? ((t & 1) ? c[3][0] : c[2][0]) : ((t & 1) ? c[1][0] : c[0][0]), y0);
                y1 = fmaf(gb, (t & 2) ? ((t & 1) ? c[3][2] : c[2][2]) : ((t & 1) ? c[1][2] : c[0][2]), y1);
                wm += 2 * WOT;
                asm volatile("{\n.reg .pred l, p, q;\n.reg .f32 n0, s0, s1, n1;\n.reg .b16 lo, hi;\n.reg .b32 w;\n"
                             "setp.ne.u32 l, %6, 0;\n"
                             "@l atom.relaxed.gpu.global.add.v4.f32 {n0, s0, s1, n1}, [%0], {%4, %2, %3, %4};\n"
                             "add.f32 s0, s0, %2;\nadd.f32 s1, s1, %3;\ncvt.rn.bf16x2.f32 w, s1, s0;\nmov.b32 {lo, hi}, w;\n"
                             "setp.eq.and.f32 p, n0, %5, l;\nsetp.eq.and.f32 q, n1, %5, l;\n"
                             "@p st.global.b16 [%1], lo;\n@q st.global.b16 [%1 + 16], hi;\n@l exit;\n}\n"
                             ::"l"(ap), "l"(op), "f"(y0), "f"(y1), "f"(1.f), "f"((float)(NCTA - 1)), "r"(br) : "memory");
            }
        }
    }
}

}

extern "C" void kernel_launch(void* const* d_in, const int* in_sizes, int n_in, void* d_out, int out_size) {
    (void)in_sizes; (void)n_in; (void)out_size;
    Params p;
    p.wq[0] = (const char*)d_in[3];
    p.wq[1] = (const char*)d_in[8];
    p.x = (const char*)d_in[0];
    p.gw = (const char*)d_in[10];
    p.kv[0] = (const char*)d_in[1] + (size_t)(SK - WA) * 512;
    p.kv[1] = (const char*)d_in[2] + (size_t)(SK - WA) * 512;
    p.kv[2] = (const char*)d_in[6];
    p.kv[3] = (const char*)d_in[7];
    p.out = (unsigned short*)d_out;
    void* sc = nullptr;
    cudaGetSymbolAddress(&sc, g_scratch);
    p.sc = (Scratch*)(((uintptr_t)sc + 32767) & ~(uintptr_t)32767);
    typedef CUresult (*EncodeFn)(CUtensorMap*, CUtensorMapDataType, cuuint32_t, void*, const cuuint64_t*, const cuuint64_t*,
                                 const cuuint32_t*, const cuuint32_t*, CUtensorMapInterleave, CUtensorMapSwizzle,
                                 CUtensorMapL2promotion, CUtensorMapFloatOOBfill);
    void* fn = nullptr;
    cudaDriverEntryPointQueryResult qr;
    cudaGetDriverEntryPoint("cuTensorMapEncodeTiled", &fn, cudaEnableDefault, &qr);
    for (int b = 0; b < 2; b++) {
        const cuuint64_t dims[2] = {64, 4096 * 7}, strides[1] = {128};
        const cuuint32_t box[2] = {64, WOT / 128}, es[2] = {1, 1};
        ((EncodeFn)fn)(&p.wo[b], CU_TENSOR_MAP_DATA_TYPE_BFLOAT16, 2, d_in[b ? 9 : 4], dims, strides, box, es,
                       CU_TENSOR_MAP_INTERLEAVE_NONE, CU_TENSOR_MAP_SWIZZLE_128B, CU_TENSOR_MAP_L2_PROMOTION_NONE,
                       CU_TENSOR_MAP_FLOAT_OOB_FILL_NONE);
    }
    cudaFuncSetAttribute(gated_mix_decode_kernel, cudaFuncAttributeMaxDynamicSharedMemorySize, SMEM_BYTES);
    gated_mix_decode_kernel<<<NCTA, NTHREADS, SMEM_BYTES>>>(p);
}
```

```cpp
#include <cuda_runtime.h>
#include <cuda.h>
#include <cuda_bf16.h>
#include <stdint.h>
#include <stddef.h>

namespace {

constexpr int DM = 448;
constexpr int SK = 8192;
constexpr int WA = 2048;
constexpr int NCTA = 128;
constexpr int TILE = 16384;
constexpr int NA = 4, NB = 16;
constexpr int NKV = 2 * (NA + NB);
constexpr int NT = NKV + 4;
constexpr int WOT = 16 * DM * 2;
constexpr int NTHREADS = 320;
constexpr int NS = 10;
constexpr int RATE0 = 1095;
constexpr int RATE = 652;
constexpr int WORATE = RATE * 7 / 8;
constexpr int STAG = 6;
constexpr int WIN = 5, WINE = 3;
constexpr int WMIN = 1;
constexpr int QWAIT = 3, OWAIT = NKV + 1;
constexpr uint32_t SPIN_LIMIT = 1u << 18;

constexpr int OFF_W    = 0;
constexpr int OFF_RING = 4 * WOT;
constexpr int QS = 576;
constexpr int OFF_Q    = OFF_RING + NS * TILE;
constexpr int OFF_S    = OFF_Q + 4 * QS;
constexpr int OFF_P    = OFF_S + 4096;
constexpr int OFF_M    = OFF_P + 2048;
constexpr int OFF_L    = OFF_M + 128;
constexpr int OFF_O    = OFF_L + 128;
constexpr int OFF_TAG  = OFF_O + 128;
constexpr int OFF_BAR  = OFF_TAG + 16;
constexpr int B_FULL = 0, B_ML = NT  , B_OREADY = B_ML + 2  , NBAR1 = B_OREADY + 2,
              B_EMPTY = NBAR1, NBAR = 2 * NBAR1;
constexpr int SMEM_BYTES = OFF_BAR + NBAR * 8;

constexpr uint32_t TAGM = 15u;
struct Scratch {
    float4 acc[2048];
    uint4 o[2][8][16][16][8];
    uint4 q[8][256];
    uint4 ml[2][8][16][2];
    unsigned int epoch[NCTA][32];
};
__device__ uint4 g_scratch[(sizeof(Scratch) + 32768) / 16];

struct Params {
    const char* wq[2];
    const char *x, *gw;
    Scratch* sc;
    unsigned short* out;
    const char* kv[4];
    CUtensorMap wo[2];
};

__device__ __forceinline__ void mbar_arrive(uint32_t bar) {
    asm volatile("mbarrier.arrive.shared::cta.b64 _, [%0];" ::"r"(bar) : "memory");
}
__device__ __forceinline__ void mbar_wait(uint32_t bar) {
    asm volatile("{\n.reg .pred p, q;\n.reg .u32 n;\nmov.u32 n, 0;\n"
                 "W:\nmbarrier.try_wait.parity.shared::cta.b64 p, [%0], 0;\nadd.u32 n, n, 1;\n"
                 "setp.lt.and.u32 q, n, %1, !p;\n@q bra W;\n}\n" ::"r"(bar), "n"(SPIN_LIMIT) : "memory");
}
__device__ __forceinline__ void ldsm4(uint32_t (&r)[4], uint32_t a) {
    asm volatile("ldmatrix.sync.aligned.m8n8.x4.shared.b16 {%0,%1,%2,%3}, [%4];"
                 : "=r"(r[0]), "=r"(r[1]), "=r"(r[2]), "=r"(r[3]) : "r"(a) : "memory");
}
__device__ __forceinline__ void ldsm4t(uint32_t (&r)[4], uint32_t a) {
    asm volatile("ldmatrix.sync.aligned.m8n8.x4.trans.shared.b16 {%0,%1,%2,%3}, [%4];"
                 : "=r"(r[0]), "=r"(r[1]), "=r"(r[2]), "=r"(r[3]) : "r"(a) : "memory");
}
__device__ __forceinline__ void mma16816(float (&c)[4], const uint32_t (&a)[4], uint32_t b0, uint32_t b1) {
    asm("mma.sync.aligned.m16n8k16.row.col.f32.bf16.bf16.f32 {%0,%1,%2,%3}, {%4,%5,%6,%7}, {%8,%9}, {%0,%1,%2,%3};"
        : "+f"(c[0]), "+f"(c[1]), "+f"(c[2]), "+f"(c[3])
        : "r"(a[0]), "r"(a[1]), "r"(a[2]), "r"(a[3]), "r"(b0), "r"(b1));
}
__device__ __forceinline__ float bf_lo(uint32_t v) { return __uint_as_float(v << 16); }
__device__ __forceinline__ float bf_hi(uint32_t v) { return __uint_as_float(v & 0xffff0000u); }
__device__ __forceinline__ uint32_t pack_bf2(float lo, float hi) {
    uint32_t r;
    asm("cvt.rn.bf16x2.f32 %0, %1, %2;" : "=r"(r) : "f"(hi), "f"(lo));
    return r;
}
__device__ __forceinline__ float round_bf(float v) { return __uint_as_float(pack_bf2(0.f, v)); }
__device__ __forceinline__ float ex2(float v) {
    float r;
    asm("ex2.approx.ftz.f32 %0, %1;" : "=f"(r) : "f"(v));
    return r;
}
__device__ __forceinline__ float rcp(float v) {
    float r;
    asm("rcp.approx.ftz.f32 %0, %1;" : "=f"(r) : "f"(v));
    return r;
}
__device__ __forceinline__ float shx(float v, int m) { return __shfl_xor_sync(0xffffffffu, v, m); }
__device__ __forceinline__ uint32_t tagged(float v, uint32_t tag) { return (__float_as_uint(v) & ~TAGM) | tag; }
__device__ __forceinline__ float untag(uint32_t v) { return __uint_as_float(v & ~TAGM); }
__device__ __forceinline__ void put2(void* p, uint32_t a, uint32_t b) {
    asm volatile("st.relaxed.gpu.global.v2.b32 [%0], {%1, %2};" ::"l"(p), "r"(a), "r"(b) : "memory");
}
template <int N>
__device__ __forceinline__ void gather(uint4 (&v)[N], const void* p, uint32_t tag) {
    uint32_t n = 0, bad;
    do {
        bad = 0;
#pragma unroll
        for (int k = 0; k < N; k++)
            asm volatile("ld.relaxed.gpu.global.v4.b32 {%0, %1, %2, %3}, [%4];"
                         : "=r"(v[k].x), "=r"(v[k].y), "=r"(v[k].z), "=r"(v[k].w) : "l"((const char*)p + 512 * k) : "memory");
#pragma unroll
        for (int k = 0; k < N; k++) bad |= (v[k].x ^ tag) | (v[k].y ^ tag) | (v[k].z ^ tag) | (v[k].w ^ tag);
    } while (__any_sync(0xffffffffu, bad & TAGM) && ++n < SPIN_LIMIT);
}
__device__ __forceinline__ uint64_t evict_first() {
    uint64_t pol;
    asm volatile("createpolicy.fractional.L2::evict_first.b64 %0, 1.0;" : "=l"(pol));
    return pol;
}

constexpr float SCALE_LOG2E = 0.0625f * 1.4426950408889634f;

__global__ void __launch_bounds__(NTHREADS, 1) gated_mix_decode_kernel(const __grid_constant__ Params p) {
    extern __shared__ __align__(1024) char smem[];
    asm volatile("prefetch.global.L2 [%0];" ::"l"(p.wq[0] + (size_t)(blockIdx.x * NTHREADS + threadIdx.x) * 32));
    uint32_t due;
    asm volatile("mov.u32 %0, %globaltimer_lo;" : "=r"(due));
    const uint32_t sb = (uint32_t)__cvta_generic_to_shared(smem);
    const uint32_t bars = sb + OFF_BAR;
    const uint32_t tid = threadIdx.x, lane = tid & 31;
    const uint32_t cta = blockIdx.x, head = cta >> 4, j = cta & 15;
    const uint32_t mi = lane >> 3, r = lane & 7;

    if (tid < 224) {
        const uint64_t pol = evict_first();
        const char* src = p.wq[j >> 3] + ((tid >> 3) * (16 * 8192) + head * 1024 + (j & 7) * 128 + r * 16);
        uint32_t dst = sb + OFF_W + (tid >> 3) * (16 * 128) + 16 * (r ^ (2 * mi));
#pragma unroll 1
        for (int i = 0; i < 8; i++) {
            asm volatile("cp.async.cg.shared.global.L2::cache_hint [%0], [%1], 16, %2;"
                         ::"r"(dst), "l"(src), "l"(pol) : "memory");
            asm volatile("cp.async.cg.shared.global.L2::cache_hint [%0], [%1], 16, %2;"
                         ::"r"(dst ^ (128 + 16)), "l"(src + 8192), "l"(pol) : "memory");
            dst += 256;
            src += 16384;
        }
    }
    const uint32_t warp = __shfl_sync(0xffffffffu, tid >> 5, 0);
    const uint32_t g = lane >> 2, t = lane & 3;

    if (warp == 9) {
        char* const sc = (char*)p.sc;
        void* const qdst = sc + (uint32_t)(offsetof(Scratch, q) + cta * 256 + (t * 8 + g) * 8);
        uint32_t tag = p.sc->epoch[cta][0];
        tag = tag == 14 ? 1 : tag + 1;
        __syncwarp();
        p.sc->epoch[cta][0] = tag;
        *(uint32_t*)(smem + OFF_TAG) = tag;
        asm volatile("bar.sync 2, 320;" ::: "memory");
        {
            float q0 = 0.f, q1 = 0.f;
#pragma unroll 1
            for (int w = 0; w < 7; w++) {
                const float4 f = *(const float4*)(smem + OFF_S + (w * 32 + lane) * 16);
                q0 += f.x; q1 += f.z;
            }
            put2(qdst, pack_bf2(0.f, q0) | tag, pack_bf2(0.f, q1) | tag);
        }
        {
            float z = 0.f;
#pragma unroll 1
            for (uint32_t i = lane; i < DM / 4; i += 32) {
                const uint2 a = __ldg((const uint2*)p.x + i), b = __ldg((const uint2*)p.gw + i);
                uint32_t m0, m1;
                asm("mul.rn.bf16x2 %0, %1, %2;" : "=r"(m0) : "r"(a.x), "r"(b.x));
                asm("mul.rn.bf16x2 %0, %1, %2;" : "=r"(m1) : "r"(a.y), "r"(b.y));
                z += (bf_lo(m0) + bf_hi(m0)) + (bf_lo(m1) + bf_hi(m1));
            }
#pragma unroll 1
            for (int s = 16; s; s >>= 1) z += shx(z, s);
            const float gate = round_bf(rcp(1.f + ex2(round_bf(z) * -1.4426950408889634f)));
            *(float2*)(smem + OFF_TAG + 8) = make_float2(gate, round_bf(1.f - gate));
        }
#pragma unroll 1
        for (int br = 0; br < 2; br++) {
            mbar_wait(bars + 8 * (B_ML + br));
            float m = ((const float*)(smem + OFF_M))[br * 16 + (lane & 15)];
            float l = ((const float*)(smem + OFF_L))[br * 16 + (lane & 15)];
#pragma unroll
            for (int s = 1; s < 8; s <<= 1) { m = fmaxf(m, shx(m, s)); l += shx(l, s); }
            if (r == 0) put2(sc + (uint32_t)(offsetof(Scratch, ml) + br * 4096 + cta * 32 + lane), tagged(m, tag), tagged(l, tag));
        }
#pragma unroll 1
        for (int br = 0; br < 2; br++) {
            uint4 ml[1], v[4];
            gather<1>(ml, sc + (uint32_t)(offsetof(Scratch, ml) + br * 4096 + head * 512 + (lane & 15) * 32), tag);
            const float m = untag((lane & 16) ? ml[0].z : ml[0].x);
            float M = m;
#pragma unroll
            for (int s = 8; s; s >>= 1) M = fmaxf(M, shx(M, s));
            const float e = ex2((m - M) * SCALE_LOG2E);
            float L = e * untag((lane & 16) ? ml[0].w : ml[0].y);
#pragma unroll
            for (int s = 8; s; s >>= 1) L += shx(L, s);
            const float wgt = e * rcp(L);
            float wk[4];
#pragma unroll
            for (int k = 0; k < 4; k++) wk[k] = __shfl_sync(0xffffffffu, wgt, 4 * (lane & 4) + 4 * k + mi);
            if (br) mbar_wait(bars + 8 * (B_FULL + OWAIT));
            gather<4>(v, sc + (uint32_t)(offsetof(Scratch, o) + br * sizeof(Scratch::o[0]) + cta * 2048 + lane * 16), tag);
            float o0 = 0.f, o1 = 0.f, o2 = 0.f, o3 = 0.f;
#pragma unroll
            for (int k = 0; k < 4; k++) {
                o0 = fmaf(wk[k], untag(v[k].x), o0); o1 = fmaf(wk[k], untag(v[k].y), o1);
                o2 = fmaf(wk[k], untag(v[k].z), o2); o3 = fmaf(wk[k], untag(v[k].w), o3);
            }
            const bool h1 = lane & 8, h2 = lane & 16;
            const float b0 = (h1 ? o2 : o0) + shx(h1 ? o0 : o2, 8);
            const float b1 = (h1 ? o3 : o1) + shx(h1 ? o1 : o3, 8);
            const float od = (h2 ? b1 : b0) + shx(h2 ? b0 : b1, 16);
            const uint32_t d = 4 * (lane & 4) + 2 * t + ((lane >> 3) & 1) + ((lane & 16) >> 1);
            ((unsigned short*)(smem + OFF_O))[br * 32 + d] = (unsigned short)pack_bf2(od, 0.f);
            __syncwarp();
            if (lane == 0) mbar_arrive(bars + 8 * (B_OREADY + br));
        }
    } else if (warp == 8) {
        if (lane == 0) {
#pragma unroll 6
            for (int i = 0; i < NBAR1; i++) {
                asm volatile("mbarrier.init.shared::cta.b64 [%0], 1;" ::"r"(bars + 8 * i) : "memory");
                asm volatile("mbarrier.init.shared::cta.b64 [%0], 8;" ::"r"(bars + 8 * (NBAR1 + i)) : "memory");
            }
            asm volatile("fence.mbarrier_init.release.cluster;" ::: "memory");
        }
        __syncwarp();
        asm volatile("bar.arrive 2, 320;" ::: "memory");
        if (lane == 0) {
            asm volatile("prefetch.tensormap [%0];" ::"l"(&p.wo[0]) : "memory");
            asm volatile("prefetch.tensormap [%0];" ::"l"(&p.wo[1]) : "memory");
            const uint64_t pol = evict_first();
            due += RATE0 + STAG * cta;
            uint32_t i = 0;
#pragma unroll 1
            for (int s = 0; s < 5; s++) {
                const bool kv = s < 4;
                const char* src = p.kv[s & 3] + (head * (SK * 512) + j * TILE);
                const uint32_t end = i + ((s & 2) ? NB : NA);
#pragma unroll 1
                for (; i < end; i++) {
                    const uint32_t full = bars + 8 * (B_FULL + i);
                    if (kv && i >= NS) mbar_wait(full + 8 * (B_EMPTY - NS));
                    if (i >= WIN) mbar_wait(full - 8 * (kv ? WIN : WINE));
                    while (true) {
                        uint32_t now, ok;
                        asm volatile("mov.u32 %0, %globaltimer_lo;" : "=r"(now));
                        asm volatile("{\n.reg .pred p;\nmbarrier.test_wait.parity.shared::cta.b64 p, [%1], 0;\nselp.u32 %0, 1, 0, p;\n}\n"
                                     : "=r"(ok) : "r"(i >= WMIN ? full - 8 * WMIN : full) : "memory");
                        if ((int)(now - due) >= 0 || ok) break;
                    }
                    asm volatile("mbarrier.arrive.expect_tx.shared::cta.b64 _, [%0], %1;" ::"r"(full), "r"(kv ? TILE : WOT) : "memory");
                    if (kv) {
                        asm volatile("cp.async.bulk.shared::cluster.global.mbarrier::complete_tx::bytes.L2::cache_hint [%0], [%1], %2, [%3], %4;"
                                     ::"r"(sb + OFF_RING + (i % NS) * TILE), "l"(src), "n"(TILE), "r"(full), "l"(pol) : "memory");
                        src += 16 * TILE;
                        due += RATE;
                    } else {
                        asm volatile("cp.async.bulk.tensor.2d.shared::cluster.global.mbarrier::complete_tx::bytes.L2::cache_hint [%0], [%1, {%2, %3}], [%4], %5;"
                                     ::"r"(sb + OFF_W + (i - NKV) * WOT), "l"(&p.wo[(i >> 1) & 1]), "r"(0),
                                       "r"((head * 32 + (i & 1) * 16 + j) * (WOT / 128)), "r"(full), "l"(pol) : "memory");
                        due += WORATE;
                    }
                }
            }
        }
    } else {
        char* const sc = (char*)p.sc;
        char* odst = sc + (uint32_t)(offsetof(Scratch, o) + (head * 16 + 2 * warp + (t & 1)) * 2048 + j * 128 + ((t >> 1) * 8 + g) * 8);
        if (warp < 7) {
            uint32_t xb[8];
            asm volatile("ld.global.nc.v4.u32 {%0, %1, %2, %3}, [%8];\nld.global.nc.v4.u32 {%4, %5, %6, %7}, [%8 + 16];\n"
                         "cp.async.wait_all;"
                         : "=r"(xb[0]), "=r"(xb[1]), "=r"(xb[2]), "=r"(xb[3]), "=r"(xb[4]), "=r"(xb[5]), "=r"(xb[6]), "=r"(xb[7])
                         : "l"(p.x + (warp * 128 + t * 32)) : "memory");
            __syncwarp();
            const uint32_t a0 = sb + OFF_W + (warp * 64 + 16 * (r >> 1) + 2 * (mi >> 1) + (r & 1)) * 128 + 16 * ((mi & 1) ^ r);
#pragma unroll 1
            for (uint32_t i = 0; i < 4; i++) {
                float c[4] = {0.f, 0.f, 0.f, 0.f};
#pragma unroll
                for (int ks = 0; ks < 4; ks++) {
                    uint32_t a[4];
                    ldsm4t(a, (a0 ^ (32 * i)) + ks * 512);
                    mma16816(c, a, xb[2 * ks], xb[2 * ks + 1]);
                }
                if (t == i) *(float4*)(smem + OFF_S + tid * 16) = make_float4(c[0], c[1], c[2], c[3]);
            }
            asm volatile("fence.proxy.async.shared::cta;" ::: "memory");
        }
        asm volatile("bar.sync 2, 320;" ::: "memory");
        const uint32_t tag = *(const uint32_t*)(smem + OFF_TAG);
        char* const ap = sc + ((tid >> 6) * 8192 + (tid & 64) * 64 + ((tid >> 4) & 3) * 1024 + (tid & 8) * 32 + (tag & 1) * 128 + r * 16);
        if (cta == 0) *(float4*)((uintptr_t)ap ^ 128) = make_float4(0.f, 0.f, 0.f, 0.f);

        const bool valid = t == (g & 3);
        const uint32_t lm0 = sb + OFF_RING + (8 * (mi >> 1) + r) * 512 + 16 * ((mi & 1) ^ (r >> 1));
        const uint32_t lm1 = lm0 ^ 32;
        {
            mbar_wait(bars + 8 * (B_FULL + QWAIT));
            uint4 v[1];
            gather<1>(v, sc + (uint32_t)(offsetof(Scratch, q) + head * 4096 + tid * 16), tag);
            uint32_t* qs = (uint32_t*)(smem + OFF_Q + (warp >> 1) * QS + (warp & 1) * 256) + g * 8 + t;
            qs[0] = __byte_perm(v[0].x, v[0].z, 0x7632);
            qs[4] = __byte_perm(v[0].y, v[0].w, 0x7632);
            asm volatile("bar.sync 1, 256;" ::: "memory");
        }
        uint32_t qa[16][4];
        {
            const uint32_t q0 = sb + OFF_Q + ((mi & 1) * 2 + (r >> 2)) * QS + 16 * ((mi >> 1) ^ (r & 3));
#pragma unroll
            for (int k = 0; k < 16; k++) ldsm4(qa[k], (q0 ^ ((k & 1) * 32)) + 64 * (k >> 1));
        }
        uint32_t T0 = 0;
#pragma unroll 1
        for (int br = 0; br < 2; br++) {
            const uint32_t nt = br ? NB : NA;
            float mx = -INFINITY;
#pragma unroll 1
            for (uint32_t kt = warp >> 1; kt < nt; kt += 4) {
                const uint32_t T = T0 + kt, off = (T % NS) * TILE + (warp & 1) * 8192;
                mbar_wait(bars + 8 * (B_FULL + T));
                float c0[4] = {0.f, 0.f, 0.f, 0.f}, c1[4] = {0.f, 0.f, 0.f, 0.f};
#pragma unroll
                for (int k = 0; k < 16; k++) {
                    uint32_t b[4];
                    ldsm4(b, ((k & 1) ? lm1 : lm0) + off + 64 * (k >> 1));
                    mma16816(c0, qa[k], b[0], b[1]);
                    mma16816(c1, qa[k], b[2], b[3]);
                }
                __syncwarp();
                if (lane == 0) asm volatile("mbarrier.arrive.shared::cta.b64 _, [%0], 4;" ::"r"(bars + 8 * (B_EMPTY + T)) : "memory");
                float4 s;
                s.x = round_bf(br ? c0[2] : c0[0]); s.y = round_bf(br ? c0[3] : c0[1]);
                s.z = round_bf(br ? c1[2] : c1[0]); s.w = round_bf(br ? c1[3] : c1[1]);
                if (valid) *(float4*)(smem + OFF_S + ((2 * kt + (warp & 1)) * 8 + g) * 16) = s;
                mx = fmaxf(fmaxf(mx, fmaxf(s.x, s.y)), fmaxf(s.z, s.w));
            }
            mx = fmaxf(mx, shx(mx, 5));
            mx = fmaxf(mx, shx(mx, 10));
            float* mred = (float*)(smem + OFF_M) + br * 16;
            if ((lane & 15) == 0) mred[(lane >> 1) + warp] = mx;
            asm volatile("bar.sync 1, 256;" ::: "memory");
            {
                const float4 m0 = *(const float4*)(mred + (lane & 4) * 2), m1 = *(const float4*)(mred + (lane & 4) * 2 + 4);
                const float M = fmaxf(fmaxf(fmaxf(m0.x, m0.y), fmaxf(m0.z, m0.w)), fmaxf(fmaxf(m1.x, m1.y), fmaxf(m1.z, m1.w)));
                const float4 s = *(const float4*)(smem + OFF_S + tid * 16);
                const uint32_t p0 = pack_bf2(ex2((s.x - M) * SCALE_LOG2E), ex2((s.y - M) * SCALE_LOG2E));
                const uint32_t p1 = pack_bf2(ex2((s.z - M) * SCALE_LOG2E), ex2((s.w - M) * SCALE_LOG2E));
                *(uint2*)(smem + OFF_P + ((tid >> 4) * 8 + r) * 16 + (tid & 8)) = make_uint2(p0, p1);
                float l = (bf_lo(p0) + bf_hi(p0)) + (bf_lo(p1) + bf_hi(p1));
                l += shx(l, 1); l += shx(l, 2); l += shx(l, 8); l += shx(l, 16);
                if ((lane & ~4) == 0) mred[(OFF_L - OFF_M) / 4 + lane * 2 + warp] = tid < nt * 16 ? l : 0.f;
            }
            asm volatile("bar.sync 1, 256;" ::: "memory");
            if (tid == 0) mbar_arrive(bars + 8 * (B_ML + br));
            T0 += nt;
            float o0[4] = {0.f, 0.f, 0.f, 0.f}, o1[4] = {0.f, 0.f, 0.f, 0.f};
#pragma unroll 1
            for (uint32_t vt = 0; vt < nt; vt++) {
                const uint32_t T = T0 + vt, off = (T % NS) * TILE + warp * 64;
                uint4 pb = make_uint4(0u, 0u, 0u, 0u);
                if (valid) pb = *(const uint4*)(smem + OFF_P + (vt * 8 + g) * 16);
                mbar_wait(bars + 8 * (B_FULL + T));
                uint32_t a[4][4];
                ldsm4t(a[0], lm0 + off);
                ldsm4t(a[1], lm1 + off);
                ldsm4t(a[2], lm0 + off + 8192);
                ldsm4t(a[3], lm1 + off + 8192);
                mma16816(o0, a[0], pb.x, pb.y);
                mma16816(o1, a[1], pb.x, pb.y);
                mma16816(o0, a[2], pb.z, pb.w);
                mma16816(o1, a[3], pb.z, pb.w);
                __syncwarp();
                if (lane == 0) mbar_arrive(bars + 8 * (B_EMPTY + T));
            }
            T0 += nt;
            const float u0 = o0[0] + o0[3] + shx(o1[0] + o1[3], 1);
            const float u1 = o0[2] + o0[1] + shx(o1[2] + o1[1], 1);
            put2(odst, tagged(u0, tag), tagged(u1, tag));
            odst += sizeof(Scratch::o[0]);
        }
        if (warp < 7) {
            uint32_t wm = sb + OFF_W + (8 * (mi >> 1) + r) * (DM * 2) + 128 * warp + 16 * ((mi & 1) ^ ((warp - r) & 7));
            unsigned short* op = p.out + (64 * warp + 16 * t + g);
            float y0 = 0.f, y1 = 0.f;
#pragma unroll 1
            for (int br = 0; br < 2; br++) {
                uint32_t ob[4], a[4][4];
                float c[4][4] = {};
                mbar_wait(bars + 8 * (B_FULL + NKV + 2 * br));
#pragma unroll
                for (int i = 0; i < 4; i++) ldsm4t(a[i], wm ^ (32 * i));
                mbar_wait(bars + 8 * (B_OREADY + br));
                const float gb = *(const float*)(smem + OFF_TAG + 8 + 4 * br);
#pragma unroll
                for (int i = 0; i < 4; i++) ob[i] = ((const uint32_t*)(smem + OFF_O))[br * 16 + 4 * i + t];
#pragma unroll
                for (int i = 0; i < 4; i++) mma16816(c[i], a[i], ob[0], ob[1]);
                asm volatile("" : "+f"(c[0][0]), "+f"(c[1][0]), "+f"(c[2][0]), "+f"(c[3][0]));
                mbar_wait(bars + 8 * (B_FULL + NKV + 2 * br + 1));
#pragma unroll
                for (int i = 0; i < 4; i++) ldsm4t(a[i], (wm ^ (32 * i)) + WOT);
#pragma unroll
                for (int i = 0; i < 4; i++) mma16816(c[i], a[i], ob[2], ob[3]);
                y0 = fmaf(gb, (t & 2) ? ((t & 1) ? c[3][0] : c[2][0]) : ((t & 1) ? c[1][0] : c[0][0]), y0);
                y1 = fmaf(gb, (t & 2) ? ((t & 1) ? c[3][2] : c[2][2]) : ((t & 1) ? c[1][2] : c[0][2]), y1);
                wm += 2 * WOT;
                asm volatile("{\n.reg .pred l, p, q;\n.reg .f32 n0, s0, s1, n1;\n.reg .b16 lo, hi;\n.reg .b32 w;\n"
                             "setp.ne.u32 l, %6, 0;\n"
                             "@l atom.relaxed.gpu.global.add.v4.f32 {n0, s0, s1, n1}, [%0], {%4, %2, %3, %4};\n"
                             "add.f32 s0, s0, %2;\nadd.f32 s1, s1, %3;\ncvt.rn.bf16x2.f32 w, s1, s0;\nmov.b32 {lo, hi}, w;\n"
                             "setp.eq.and.f32 p, n0, %5, l;\nsetp.eq.and.f32 q, n1, %5, l;\n"
                             "@p st.global.b16 [%1], lo;\n@q st.global.b16 [%1 + 16], hi;\n@l exit;\n}\n"
                             ::"l"(ap), "l"(op), "f"(y0), "f"(y1), "f"(1.f), "f"((float)(NCTA - 1)), "r"(br) : "memory");
            }
        }
    }
}

}

extern "C" void kernel_launch(void* const* d_in, const int* in_sizes, int n_in, void* d_out, int out_size) {
    (void)in_sizes; (void)n_in; (void)out_size;
    Params p;
    p.wq[0] = (const char*)d_in[3];
    p.wq[1] = (const char*)d_in[8];
    p.x = (const char*)d_in[0];
    p.gw = (const char*)d_in[10];
    p.kv[0] = (const char*)d_in[1] + (size_t)(SK - WA) * 512;
    p.kv[1] = (const char*)d_in[2] + (size_t)(SK - WA) * 512;
    p.kv[2] = (const char*)d_in[6];
    p.kv[3] = (const char*)d_in[7];
    p.out = (unsigned short*)d_out;
    void* sc = nullptr;
    cudaGetSymbolAddress(&sc, g_scratch);
    p.sc = (Scratch*)(((uintptr_t)sc + 32767) & ~(uintptr_t)32767);
    typedef CUresult (*EncodeFn)(CUtensorMap*, CUtensorMapDataType, cuuint32_t, void*, const cuuint64_t*, const cuuint64_t*,
                                 const cuuint32_t*, const cuuint32_t*, CUtensorMapInterleave, CUtensorMapSwizzle,
                                 CUtensorMapL2promotion, CUtensorMapFloatOOBfill);
    void* fn = nullptr;
    cudaDriverEntryPointQueryResult qr;
    cudaGetDriverEntryPoint("cuTensorMapEncodeTiled", &fn, cudaEnableDefault, &qr);
    for (int b = 0; b < 2; b++) {
        const cuuint64_t dims[2] = {64, 4096 * 7}, strides[1] = {128};
        const cuuint32_t box[2] = {64, WOT / 128}, es[2] = {1, 1};
        ((EncodeFn)fn)(&p.wo[b], CU_TENSOR_MAP_DATA_TYPE_BFLOAT16, 2, d_in[b ? 9 : 4], dims, strides, box, es,
                       CU_TENSOR_MAP_INTERLEAVE_NONE, CU_TENSOR_MAP_SWIZZLE_128B, CU_TENSOR_MAP_L2_PROMOTION_NONE,
                       CU_TENSOR_MAP_FLOAT_OOB_FILL_NONE);
    }
    cudaFuncSetAttribute(gated_mix_decode_kernel, cudaFuncAttributeMaxDynamicSharedMemorySize, SMEM_BYTES);
    gated_mix_decode_kernel<<<NCTA, NTHREADS, SMEM_BYTES>>>(p);
}
```

```cpp
#include <cuda_runtime.h>
#include <cuda.h>
#include <cuda_bf16.h>
#include <stdint.h>
#include <stddef.h>

namespace {

constexpr int DM = 448;
constexpr int SK = 8192;
constexpr int WA = 2048;
constexpr int NCTA = 128;
constexpr int TILE = 16384;
constexpr int NA = 4, NB = 16;
constexpr int NKV = 2 * (NA + NB);
constexpr int NT = NKV + 4;
constexpr int WOT = 16 * DM * 2;
constexpr int NTHREADS = 320;
constexpr int NS = 10;
constexpr int RATE0 = 1105;
constexpr int RATE = 652;
constexpr int WORATE = RATE * 7 / 8;
constexpr int STAG = 6;
constexpr int WIN = 5, WINE = 3;
constexpr int WMIN = 1;
constexpr int QWAIT = 3, OWAIT = NKV, ODELAY = 500;
constexpr uint32_t SPIN_LIMIT = 1u << 18;

constexpr int OFF_W    = 0;
constexpr int OFF_RING = 4 * WOT;
constexpr int QS = 576;
constexpr int OFF_Q    = OFF_RING + NS * TILE;
constexpr int OFF_S    = OFF_Q + 4 * QS;
constexpr int OFF_P    = OFF_S + 4096;
constexpr int OFF_M    = OFF_P + 2048;
constexpr int OFF_L    = OFF_M + 128;
constexpr int OFF_O    = OFF_L + 128;
constexpr int OFF_TAG  = OFF_O + 128;
constexpr int OFF_BAR  = OFF_TAG + 16;
constexpr int B_FULL = 0, B_ML = NT  , B_OREADY = B_ML + 2  , NBAR1 = B_OREADY + 2,
              B_EMPTY = NBAR1, NBAR = 2 * NBAR1;
constexpr int SMEM_BYTES = OFF_BAR + NBAR * 8;

constexpr uint32_t TAGM = 15u;
struct Scratch {
    float4 acc[2048];
    uint4 o[2][8][16][16][8];
    uint4 q[8][256];
    uint4 ml[2][8][16][2];
    unsigned int epoch[NCTA][32];
};
__device__ uint4 g_scratch[(sizeof(Scratch) + 32768) / 16];

struct Params {
    const char* wq[2];
    const char *x, *gw;
    Scratch* sc;
    unsigned short* out;
    const char* kv[4];
    CUtensorMap wo[2];
};

__device__ __forceinline__ void mbar_arrive(uint32_t bar) {
    asm volatile("mbarrier.arrive.shared::cta.b64 _, [%0];" ::"r"(bar) : "memory");
}
__device__ __forceinline__ void mbar_wait(uint32_t bar) {
    asm volatile("{\n.reg .pred p, q;\n.reg .u32 n;\nmov.u32 n, 0;\n"
                 "W:\nmbarrier.try_wait.parity.shared::cta.b64 p, [%0], 0;\nadd.u32 n, n, 1;\n"
                 "setp.lt.and.u32 q, n, %1, !p;\n@q bra W;\n}\n" ::"r"(bar), "n"(SPIN_LIMIT) : "memory");
}
__device__ __forceinline__ uint32_t now_ns() {
    uint32_t t;
    asm volatile("mov.u32 %0, %globaltimer_lo;" : "=r"(t));
    return t;
}
__device__ __forceinline__ void wait_time_or(uint32_t due, uint32_t bar) {
#pragma unroll 1
    for (uint32_t n = 0; n < SPIN_LIMIT; n++) {
        const uint32_t now = now_ns();
        uint32_t ok;
        asm volatile("{\n.reg .pred p;\nmbarrier.test_wait.parity.shared::cta.b64 p, [%1], 0;\nselp.u32 %0, 1, 0, p;\n}\n"
                     : "=r"(ok) : "r"(bar) : "memory");
        if ((int)(now - due) >= 0 || ok) break;
    }
}
__device__ __forceinline__ void ldsm4(uint32_t (&r)[4], uint32_t a) {
    asm volatile("ldmatrix.sync.aligned.m8n8.x4.shared.b16 {%0,%1,%2,%3}, [%4];"
                 : "=r"(r[0]), "=r"(r[1]), "=r"(r[2]), "=r"(r[3]) : "r"(a) : "memory");
}
__device__ __forceinline__ void ldsm4t(uint32_t (&r)[4], uint32_t a) {
    asm volatile("ldmatrix.sync.aligned.m8n8.x4.trans.shared.b16 {%0,%1,%2,%3}, [%4];"
                 : "=r"(r[0]), "=r"(r[1]), "=r"(r[2]), "=r"(r[3]) : "r"(a) : "memory");
}
__device__ __forceinline__ void mma16816(float (&c)[4], const uint32_t (&a)[4], uint32_t b0, uint32_t b1) {
    asm("mma.sync.aligned.m16n8k16.row.col.f32.bf16.bf16.f32 {%0,%1,%2,%3}, {%4,%5,%6,%7}, {%8,%9}, {%0,%1,%2,%3};"
        : "+f"(c[0]), "+f"(c[1]), "+f"(c[2]), "+f"(c[3])
        : "r"(a[0]), "r"(a[1]), "r"(a[2]), "r"(a[3]), "r"(b0), "r"(b1));
}
__device__ __forceinline__ float bf_lo(uint32_t v) { return __uint_as_float(v << 16); }
__device__ __forceinline__ float bf_hi(uint32_t v) { return __uint_as_float(v & 0xffff0000u); }
__device__ __forceinline__ uint32_t pack_bf2(float lo, float hi) {
    uint32_t r;
    asm("cvt.rn.bf16x2.f32 %0, %1, %2;" : "=r"(r) : "f"(hi), "f"(lo));
    return r;
}
__device__ __forceinline__ float round_bf(float v) { return __uint_as_float(pack_bf2(0.f, v)); }
__device__ __forceinline__ float ex2(float v) {
    float r;
    asm("ex2.approx.ftz.f32 %0, %1;" : "=f"(r) : "f"(v));
    return r;
}
__device__ __forceinline__ float rcp(float v) {
    float r;
    asm("rcp.approx.ftz.f32 %0, %1;" : "=f"(r) : "f"(v));
    return r;
}
__device__ __forceinline__ float shx(float v, int m) { return __shfl_xor_sync(0xffffffffu, v, m); }
__device__ __forceinline__ uint32_t tagged(float v, uint32_t tag) { return (__float_as_uint(v) & ~TAGM) | tag; }
__device__ __forceinline__ float untag(uint32_t v) { return __uint_as_float(v & ~TAGM); }
__device__ __forceinline__ void put2(void* p, uint32_t a, uint32_t b) {
    asm volatile("st.relaxed.gpu.global.v2.b32 [%0], {%1, %2};" ::"l"(p), "r"(a), "r"(b) : "memory");
}
template <int N>
__device__ __forceinline__ void gather(uint4 (&v)[N], const void* p, uint32_t tag) {
    uint32_t n = 0, bad;
    do {
        bad = 0;
#pragma unroll
        for (int k = 0; k < N; k++)
            asm volatile("ld.relaxed.gpu.global.v4.b32 {%0, %1, %2, %3}, [%4];"
                         : "=r"(v[k].x), "=r"(v[k].y), "=r"(v[k].z), "=r"(v[k].w) : "l"((const char*)p + 512 * k) : "memory");
#pragma unroll
        for (int k = 0; k < N; k++) bad |= (v[k].x ^ tag) | (v[k].y ^ tag) | (v[k].z ^ tag) | (v[k].w ^ tag);
    } while (__any_sync(0xffffffffu, bad & TAGM) && ++n < SPIN_LIMIT);
}
__device__ __forceinline__ uint64_t evict_first() {
    uint64_t pol;
    asm volatile("createpolicy.fractional.L2::evict_first.b64 %0, 1.0;" : "=l"(pol));
    return pol;
}

constexpr float SCALE_LOG2E = 0.0625f * 1.4426950408889634f;

__global__ void __launch_bounds__(NTHREADS, 1) gated_mix_decode_kernel(const __grid_constant__ Params p) {
    extern __shared__ __align__(1024) char smem[];
    asm volatile("prefetch.global.L2 [%0];" ::"l"(p.wq[0] + (size_t)(blockIdx.x * NTHREADS + threadIdx.x) * 32));
    uint32_t due = now_ns();
    const uint32_t sb = (uint32_t)__cvta_generic_to_shared(smem);
    const uint32_t bars = sb + OFF_BAR;
    const uint32_t tid = threadIdx.x, lane = tid & 31;
    const uint32_t cta = blockIdx.x, head = cta >> 4, j = cta & 15;
    const uint32_t mi = lane >> 3, r = lane & 7;

    if (tid < 224) {
        const uint64_t pol = evict_first();
        const char* src = p.wq[j >> 3] + ((tid >> 3) * (16 * 8192) + head * 1024 + (j & 7) * 128 + r * 16);
        uint32_t dst = sb + OFF_W + (tid >> 3) * (16 * 128) + 16 * (r ^ (2 * mi));
#pragma unroll 1
        for (int i = 0; i < 8; i++) {
            asm volatile("cp.async.cg.shared.global.L2::cache_hint [%0], [%1], 16, %2;"
                         ::"r"(dst), "l"(src), "l"(pol) : "memory");
            asm volatile("cp.async.cg.shared.global.L2::cache_hint [%0], [%1], 16, %2;"
                         ::"r"(dst ^ (128 + 16)), "l"(src + 8192), "l"(pol) : "memory");
            dst += 256;
            src += 16384;
        }
    }
    const uint32_t warp = __shfl_sync(0xffffffffu, tid >> 5, 0);
    const uint32_t g = lane >> 2, t = lane & 3;

    if (warp == 9) {
        char* const sc = (char*)p.sc;
        void* const qdst = sc + (uint32_t)(offsetof(Scratch, q) + cta * 256 + (t * 8 + g) * 8);
        uint32_t tag = p.sc->epoch[cta][0];
        tag = tag == 14 ? 1 : tag + 1;
        __syncwarp();
        p.sc->epoch[cta][0] = tag;
        *(uint32_t*)(smem + OFF_TAG) = tag;
        asm volatile("bar.sync 2, 320;" ::: "memory");
        {
            float q0 = 0.f, q1 = 0.f;
#pragma unroll 1
            for (int w = 0; w < 7; w++) {
                const float4 f = *(const float4*)(smem + OFF_S + (w * 32 + lane) * 16);
                q0 += f.x; q1 += f.z;
            }
            put2(qdst, pack_bf2(0.f, q0) | tag, pack_bf2(0.f, q1) | tag);
            asm volatile("bar.arrive 3, 288;" ::: "memory");
        }
        {
            float z = 0.f;
#pragma unroll 1
            for (uint32_t i = lane; i < DM / 4; i += 32) {
                const uint2 a = __ldg((const uint2*)p.x + i), b = __ldg((const uint2*)p.gw + i);
                uint32_t m0, m1;
                asm("mul.rn.bf16x2 %0, %1, %2;" : "=r"(m0) : "r"(a.x), "r"(b.x));
                asm("mul.rn.bf16x2 %0, %1, %2;" : "=r"(m1) : "r"(a.y), "r"(b.y));
                z += (bf_lo(m0) + bf_hi(m0)) + (bf_lo(m1) + bf_hi(m1));
            }
#pragma unroll 1
            for (int s = 16; s; s >>= 1) z += shx(z, s);
            const float gate = round_bf(rcp(1.f + ex2(round_bf(z) * -1.4426950408889634f)));
            *(float2*)(smem + OFF_TAG + 8) = make_float2(gate, round_bf(1.f - gate));
        }
#pragma unroll 1
        for (int br = 0; br < 2; br++) {
            mbar_wait(bars + 8 * (B_ML + br));
            float m = ((const float*)(smem + OFF_M))[br * 16 + (lane & 15)];
            float l = ((const float*)(smem + OFF_L))[br * 16 + (lane & 15)];
#pragma unroll
            for (int s = 1; s < 8; s <<= 1) { m = fmaxf(m, shx(m, s)); l += shx(l, s); }
            if (r == 0) put2(sc + (uint32_t)(offsetof(Scratch, ml) + br * 4096 + cta * 32 + lane), tagged(m, tag), tagged(l, tag));
        }
#pragma unroll 1
        for (int br = 0; br < 2; br++) {
            uint4 ml[1], v[4];
            gather<1>(ml, sc + (uint32_t)(offsetof(Scratch, ml) + br * 4096 + head * 512 + (lane & 15) * 32), tag);
            const float m = untag((lane & 16) ? ml[0].z : ml[0].x);
            float M = m;
#pragma unroll
            for (int s = 8; s; s >>= 1) M = fmaxf(M, shx(M, s));
            const float e = ex2((m - M) * SCALE_LOG2E);
            float L = e * untag((lane & 16) ? ml[0].w : ml[0].y);
#pragma unroll
            for (int s = 8; s; s >>= 1) L += shx(L, s);
            const float wgt = e * rcp(L);
            float wk[4];
#pragma unroll
            for (int k = 0; k < 4; k++) wk[k] = __shfl_sync(0xffffffffu, wgt, 4 * (lane & 4) + 4 * k + mi);
            if (br) {
                mbar_wait(bars + 8 * (B_FULL + OWAIT));
                wait_time_or(now_ns() + ODELAY, bars + 8 * (B_FULL + OWAIT + 1));
            }
            gather<4>(v, sc + (uint32_t)(offsetof(Scratch, o) + br * sizeof(Scratch::o[0]) + cta * 2048 + lane * 16), tag);
            float o0 = 0.f, o1 = 0.f, o2 = 0.f, o3 = 0.f;
#pragma unroll
            for (int k = 0; k < 4; k++) {
                o0 = fmaf(wk[k], untag(v[k].x), o0); o1 = fmaf(wk[k], untag(v[k].y), o1);
                o2 = fmaf(wk[k], untag(v[k].z), o2); o3 = fmaf(wk[k], untag(v[k].w), o3);
            }
            const bool h1 = lane & 8, h2 = lane & 16;
            const float b0 = (h1 ? o2 : o0) + shx(h1 ? o0 : o2, 8);
            const float b1 = (h1 ? o3 : o1) + shx(h1 ? o1 : o3, 8);
            const float od = (h2 ? b1 : b0) + shx(h2 ? b0 : b1, 16);
            const uint32_t d = 4 * (lane & 4) + 2 * t + ((lane >> 3) & 1) + ((lane & 16) >> 1);
            ((unsigned short*)(smem + OFF_O))[br * 32 + d] = (unsigned short)pack_bf2(od, 0.f);
            __syncwarp();
            if (lane == 0) mbar_arrive(bars + 8 * (B_OREADY + br));
        }
    } else if (warp == 8) {
        if (lane == 0) {
#pragma unroll 6
            for (int i = 0; i < NBAR1; i++) {
                asm volatile("mbarrier.init.shared::cta.b64 [%0], 1;" ::"r"(bars + 8 * i) : "memory");
                asm volatile("mbarrier.init.shared::cta.b64 [%0], 8;" ::"r"(bars + 8 * (NBAR1 + i)) : "memory");
            }
            asm volatile("fence.mbarrier_init.release.cluster;" ::: "memory");
        }
        __syncwarp();
        asm volatile("bar.arrive 2, 320;" ::: "memory");
        if (lane == 0) {
            asm volatile("prefetch.tensormap [%0];" ::"l"(&p.wo[0]) : "memory");
            asm volatile("prefetch.tensormap [%0];" ::"l"(&p.wo[1]) : "memory");
            const uint64_t pol = evict_first();
            due += RATE0 + STAG * cta;
            uint32_t i = 0;
#pragma unroll 1
            for (int s = 0; s < 5; s++) {
                const bool kv = s < 4;
                const char* src = p.kv[s & 3] + (head * (SK * 512) + j * TILE);
                const uint32_t end = i + ((s & 2) ? NB : NA);
#pragma unroll 1
                for (; i < end; i++) {
                    const uint32_t full = bars + 8 * (B_FULL + i);
                    if (kv && i >= NS) mbar_wait(full + 8 * (B_EMPTY - NS));
                    if (i >= WIN) mbar_wait(full - 8 * (kv ? WIN : WINE));
                    wait_time_or(due, i >= WMIN ? full - 8 * WMIN : full);
                    asm volatile("mbarrier.arrive.expect_tx.shared::cta.b64 _, [%0], %1;" ::"r"(full), "r"(kv ? TILE : WOT) : "memory");
                    if (kv) {
                        asm volatile("cp.async.bulk.shared::cluster.global.mbarrier::complete_tx::bytes.L2::cache_hint [%0], [%1], %2, [%3], %4;"
                                     ::"r"(sb + OFF_RING + (i % NS) * TILE), "l"(src), "n"(TILE), "r"(full), "l"(pol) : "memory");
                        src += 16 * TILE;
                        due += RATE;
                    } else {
                        asm volatile("cp.async.bulk.tensor.2d.shared::cluster.global.mbarrier::complete_tx::bytes.L2::cache_hint [%0], [%1, {%2, %3}], [%4], %5;"
                                     ::"r"(sb + OFF_W + (i - NKV) * WOT), "l"(&p.wo[(i >> 1) & 1]), "r"(0),
                                       "r"((head * 32 + (i & 1) * 16 + j) * (WOT / 128)), "r"(full), "l"(pol) : "memory");
                        due += WORATE;
                    }
                }
            }
        }
        __syncwarp();
    } else {
        char* const sc = (char*)p.sc;
        char* odst = sc + (uint32_t)(offsetof(Scratch, o) + (head * 16 + 2 * warp + (t & 1)) * 2048 + j * 128 + ((t >> 1) * 8 + g) * 8);
        if (warp < 7) {
            uint32_t xb[8];
            asm volatile("ld.global.nc.v4.u32 {%0, %1, %2, %3}, [%8];\nld.global.nc.v4.u32 {%4, %5, %6, %7}, [%8 + 16];\n"
                         "cp.async.wait_all;"
                         : "=r"(xb[0]), "=r"(xb[1]), "=r"(xb[2]), "=r"(xb[3]), "=r"(xb[4]), "=r"(xb[5]), "=r"(xb[6]), "=r"(xb[7])
                         : "l"(p.x + (warp * 128 + t * 32)) : "memory");
            __syncwarp();
            const uint32_t a0 = sb + OFF_W + (warp * 64 + 16 * (r >> 1) + 2 * (mi >> 1) + (r & 1)) * 128 + 16 * ((mi & 1) ^ r);
#pragma unroll 1
            for (uint32_t i = 0; i < 4; i++) {
                float c[4] = {0.f, 0.f, 0.f, 0.f};
#pragma unroll
                for (int ks = 0; ks < 4; ks++) {
                    uint32_t a[4];
                    ldsm4t(a, (a0 ^ (32 * i)) + ks * 512);
                    mma16816(c, a, xb[2 * ks], xb[2 * ks + 1]);
                }
                if (t == i) *(float4*)(smem + OFF_S + tid * 16) = make_float4(c[0], c[1], c[2], c[3]);
            }
            asm volatile("fence.proxy.async.shared::cta;" ::: "memory");
        }
        asm volatile("bar.sync 2, 320;" ::: "memory");
        const uint32_t tag = *(const uint32_t*)(smem + OFF_TAG);
        char* const ap = sc + ((tid >> 6) * 8192 + (tid & 64) * 64 + ((tid >> 4) & 3) * 1024 + (tid & 8) * 32 + (tag & 1) * 128 + r * 16);
        if (cta == 0) *(float4*)((uintptr_t)ap ^ 128) = make_float4(0.f, 0.f, 0.f, 0.f);

        const bool valid = t == (g & 3);
        const uint32_t lm0 = sb + OFF_RING + (8 * (mi >> 1) + r) * 512 + 16 * ((mi & 1) ^ (r >> 1));
        const uint32_t lm1 = lm0 ^ 32;
        {
            mbar_wait(bars + 8 * (B_FULL + QWAIT));
            uint4 v[1];
            gather<1>(v, sc + (uint32_t)(offsetof(Scratch, q) + head * 4096 + tid * 16), tag);
            uint32_t* qs = (uint32_t*)(smem + OFF_Q + (warp >> 1) * QS + (warp & 1) * 256) + g * 8 + t;
            qs[0] = __byte_perm(v[0].x, v[0].z, 0x7632);
            qs[4] = __byte_perm(v[0].y, v[0].w, 0x7632);
            asm volatile("bar.sync 3, 288;" ::: "memory");
        }
        uint32_t qa[16][4];
        {
            const uint32_t q0 = sb + OFF_Q + ((mi & 1) * 2 + (r >> 2)) * QS + 16 * ((mi >> 1) ^ (r & 3));
#pragma unroll
            for (int k = 0; k < 16; k++) ldsm4(qa[k], (q0 ^ ((k & 1) * 32)) + 64 * (k >> 1));
        }
        uint32_t T0 = 0;
#pragma unroll 1
        for (int br = 0; br < 2; br++) {
            const uint32_t nt = br ? NB : NA;
            float mx = -INFINITY;
#pragma unroll 1
            for (uint32_t kt = warp >> 1; kt < nt; kt += 4) {
                const uint32_t T = T0 + kt, off = (T % NS) * TILE + (warp & 1) * 8192;
                mbar_wait(bars + 8 * (B_FULL + T));
                float c0[4] = {0.f, 0.f, 0.f, 0.f}, c1[4] = {0.f, 0.f, 0.f, 0.f};
#pragma unroll
                for (int k = 0; k < 16; k++) {
                    uint32_t b[4];
                    ldsm4(b, ((k & 1) ? lm1 : lm0) + off + 64 * (k >> 1));
                    mma16816(c0, qa[k], b[0], b[1]);
                    mma16816(c1, qa[k], b[2], b[3]);
                }
                __syncwarp();
                if (lane == 0) asm volatile("mbarrier.arrive.shared::cta.b64 _, [%0], 4;" ::"r"(bars + 8 * (B_EMPTY + T)) : "memory");
                float4 s;
                s.x = round_bf(br ? c0[2] : c0[0]); s.y = round_bf(br ? c0[3] : c0[1]);
                s.z = round_bf(br ? c1[2] : c1[0]); s.w = round_bf(br ? c1[3] : c1[1]);
                if (valid) *(float4*)(smem + OFF_S + ((2 * kt + (warp & 1)) * 8 + g) * 16) = s;
                mx = fmaxf(fmaxf(mx, fmaxf(s.x, s.y)), fmaxf(s.z, s.w));
            }
            mx = fmaxf(mx, shx(mx, 5));
            mx = fmaxf(mx, shx(mx, 10));
            float* mred = (float*)(smem + OFF_M) + br * 16;
            if ((lane & 15) == 0) mred[(lane >> 1) + warp] = mx;
            asm volatile("bar.sync 1, 256;" ::: "memory");
            {
                const float4 m0 = *(const float4*)(mred + (lane & 4) * 2), m1 = *(const float4*)(mred + (lane & 4) * 2 + 4);
                const float M = fmaxf(fmaxf(fmaxf(m0.x, m0.y), fmaxf(m0.z, m0.w)), fmaxf(fmaxf(m1.x, m1.y), fmaxf(m1.z, m1.w)));
                const float4 s = *(const float4*)(smem + OFF_S + tid * 16);
                const uint32_t p0 = pack_bf2(ex2((s.x - M) * SCALE_LOG2E), ex2((s.y - M) * SCALE_LOG2E));
                const uint32_t p1 = pack_bf2(ex2((s.z - M) * SCALE_LOG2E), ex2((s.w - M) * SCALE_LOG2E));
                *(uint2*)(smem + OFF_P + ((tid >> 4) * 8 + r) * 16 + (tid & 8)) = make_uint2(p0, p1);
                float l = (bf_lo(p0) + bf_hi(p0)) + (bf_lo(p1) + bf_hi(p1));
                l += shx(l, 1); l += shx(l, 2); l += shx(l, 8); l += shx(l, 16);
                if ((lane & ~4) == 0) mred[(OFF_L - OFF_M) / 4 + lane * 2 + warp] = tid < nt * 16 ? l : 0.f;
            }
            asm volatile("bar.sync 1, 256;" ::: "memory");
            if (tid == 0) mbar_arrive(bars + 8 * (B_ML + br));
            T0 += nt;
            float o0[4] = {0.f, 0.f, 0.f, 0.f}, o1[4] = {0.f, 0.f, 0.f, 0.f};
#pragma unroll 1
            for (uint32_t vt = 0; vt < nt; vt++) {
                const uint32_t T = T0 + vt, off = (T % NS) * TILE + warp * 64;
                uint4 pb = make_uint4(0u, 0u, 0u, 0u);
                if (valid) pb = *(const uint4*)(smem + OFF_P + (vt * 8 + g) * 16);
                mbar_wait(bars + 8 * (B_FULL + T));
                uint32_t a[4][4];
                ldsm4t(a[0], lm0 + off);
                ldsm4t(a[1], lm1 + off);
                ldsm4t(a[2], lm0 + off + 8192);
                ldsm4t(a[3], lm1 + off + 8192);
                mma16816(o0, a[0], pb.x, pb.y);
                mma16816(o1, a[1], pb.x, pb.y);
                mma16816(o0, a[2], pb.z, pb.w);
                mma16816(o1, a[3], pb.z, pb.w);
                __syncwarp();
                if (lane == 0) mbar_arrive(bars + 8 * (B_EMPTY + T));
            }
            T0 += nt;
            const float u0 = o0[0] + o0[3] + shx(o1[0] + o1[3], 1);
            const float u1 = o0[2] + o0[1] + shx(o1[2] + o1[1], 1);
            put2(odst, tagged(u0, tag), tagged(u1, tag));
            odst += sizeof(Scratch::o[0]);
        }
        if (warp < 7) {
            uint32_t wm = sb + OFF_W + (8 * (mi >> 1) + r) * (DM * 2) + 128 * warp + 16 * ((mi & 1) ^ ((warp - r) & 7));
            unsigned short* op = p.out + (64 * warp + 16 * t + g);
            float y0 = 0.f, y1 = 0.f;
#pragma unroll 1
            for (int br = 0; br < 2; br++) {
                uint32_t ob[4], a[4][4];
                float c[4][4] = {};
                mbar_wait(bars + 8 * (B_FULL + NKV + 2 * br));
#pragma unroll
                for (int i = 0; i < 4; i++) ldsm4t(a[i], wm ^ (32 * i));
                mbar_wait(bars + 8 * (B_OREADY + br));
                const float gb = *(const float*)(smem + OFF_TAG + 8 + 4 * br);
#pragma unroll
                for (int i = 0; i < 4; i++) ob[i] = ((const uint32_t*)(smem + OFF_O))[br * 16 + 4 * i + t];
#pragma unroll
                for (int i = 0; i < 4; i++) mma16816(c[i], a[i], ob[0], ob[1]);
                asm volatile("" : "+f"(c[0][0]), "+f"(c[1][0]), "+f"(c[2][0]), "+f"(c[3][0]));
                mbar_wait(bars + 8 * (B_FULL + NKV + 2 * br + 1));
#pragma unroll
                for (int i = 0; i < 4; i++) ldsm4t(a[i], (wm ^ (32 * i)) + WOT);
#pragma unroll
                for (int i = 0; i < 4; i++) mma16816(c[i], a[i], ob[2], ob[3]);
                y0 = fmaf(gb, (t & 2) ? ((t & 1) ? c[3][0] : c[2][0]) : ((t & 1) ? c[1][0] : c[0][0]), y0);
                y1 = fmaf(gb, (t & 2) ? ((t & 1) ? c[3][2] : c[2][2]) : ((t & 1) ? c[1][2] : c[0][2]), y1);
                wm += 2 * WOT;
                asm volatile("{\n.reg .pred l, p, q;\n.reg .f32 n0, s0, s1, n1;\n.reg .b16 lo, hi;\n.reg .b32 w;\n"
                             "setp.ne.u32 l, %6, 0;\n"
                             "@l atom.relaxed.gpu.global.add.v4.f32 {n0, s0, s1, n1}, [%0], {%4, %2, %3, %4};\n"
                             "add.f32 s0, s0, %2;\nadd.f32 s1, s1, %3;\ncvt.rn.bf16x2.f32 w, s1, s0;\nmov.b32 {lo, hi}, w;\n"
                             "setp.eq.and.f32 p, n0, %5, l;\nsetp.eq.and.f32 q, n1, %5, l;\n"
                             "@p st.global.b16 [%1], lo;\n@q st.global.b16 [%1 + 16], hi;\n@l exit;\n}\n"
                             ::"l"(ap), "l"(op), "f"(y0), "f"(y1), "f"(1.f), "f"((float)(NCTA - 1)), "r"(br) : "memory");
            }
        }
    }
}

}

extern "C" void kernel_launch(void* const* d_in, const int* in_sizes, int n_in, void* d_out, int out_size) {
    (void)in_sizes; (void)n_in; (void)out_size;
    Params p;
    p.wq[0] = (const char*)d_in[3];
    p.wq[1] = (const char*)d_in[8];
    p.x = (const char*)d_in[0];
    p.gw = (const char*)d_in[10];
    p.kv[0] = (const char*)d_in[1] + (size_t)(SK - WA) * 512;
    p.kv[1] = (const char*)d_in[2] + (size_t)(SK - WA) * 512;
    p.kv[2] = (const char*)d_in[6];
    p.kv[3] = (const char*)d_in[7];
    p.out = (unsigned short*)d_out;
    void* sc = nullptr;
    cudaGetSymbolAddress(&sc, g_scratch);
    p.sc = (Scratch*)(((uintptr_t)sc + 32767) & ~(uintptr_t)32767);
    typedef CUresult (*EncodeFn)(CUtensorMap*, CUtensorMapDataType, cuuint32_t, void*, const cuuint64_t*, const cuuint64_t*,
                                 const cuuint32_t*, const cuuint32_t*, CUtensorMapInterleave, CUtensorMapSwizzle,
                                 CUtensorMapL2promotion, CUtensorMapFloatOOBfill);
    void* fn = nullptr;
    cudaDriverEntryPointQueryResult qr;
    cudaGetDriverEntryPoint("cuTensorMapEncodeTiled", &fn, cudaEnableDefault, &qr);
    for (int b = 0; b < 2; b++) {
        const cuuint64_t dims[2] = {64, 4096 * 7}, strides[1] = {128};
        const cuuint32_t box[2] = {64, WOT / 128}, es[2] = {1, 1};
        ((EncodeFn)fn)(&p.wo[b], CU_TENSOR_MAP_DATA_TYPE_BFLOAT16, 2, d_in[b ? 9 : 4], dims, strides, box, es,
                       CU_TENSOR_MAP_INTERLEAVE_NONE, CU_TENSOR_MAP_SWIZZLE_128B, CU_TENSOR_MAP_L2_PROMOTION_NONE,
                       CU_TENSOR_MAP_FLOAT_OOB_FILL_NONE);
    }
    cudaFuncSetAttribute(gated_mix_decode_kernel, cudaFuncAttributeMaxDynamicSharedMemorySize, SMEM_BYTES);
    gated_mix_decode_kernel<<<NCTA, NTHREADS, SMEM_BYTES>>>(p);
}
```

```cpp
#include <cuda_runtime.h>
#include <cuda.h>
#include <cuda_bf16.h>
#include <stdint.h>
#include <stddef.h>

namespace {

constexpr int DM = 448;
constexpr int SK = 8192;
constexpr int WA = 2048;
constexpr int NCTA = 128;
constexpr int TILE = 16384;
constexpr int NA = 4, NB = 16;
constexpr int NKV = 2 * (NA + NB);
constexpr int NT = NKV + 4;
constexpr int WOT = 16 * DM * 2;
constexpr int NTHREADS = 320;
constexpr int NS = 10;
constexpr int RATE0 = 1105;
constexpr int RATE = 652;
constexpr int WORATE = RATE * 7 / 8;
constexpr int STAG = 6;
constexpr int WIN = 5, WINE = 3;
constexpr int WMIN = 1;
constexpr int QWAIT = 3, OWAIT = NKV, ODELAY = 500;
constexpr uint32_t SPIN_LIMIT = 1u << 18;

constexpr int OFF_W    = 0;
constexpr int OFF_RING = 4 * WOT;
constexpr int QS = 576;
constexpr int OFF_Q    = OFF_RING + NS * TILE;
constexpr int OFF_S    = OFF_Q + 4 * QS;
constexpr int OFF_P    = OFF_S + 4096;
constexpr int OFF_M    = OFF_P + 2048;
constexpr int OFF_L    = OFF_M + 128;
constexpr int OFF_O    = OFF_L + 128;
constexpr int OFF_TAG  = OFF_O + 128;
constexpr int OFF_BAR  = OFF_TAG + 16;
constexpr int B_FULL = 0, B_ML = NT  , B_OREADY = B_ML + 2  , NBAR1 = B_OREADY + 2,
              B_EMPTY = NBAR1, NBAR = 2 * NBAR1;
constexpr int SMEM_BYTES = OFF_BAR + NBAR * 8;

constexpr uint32_t TAGM = 15u;
struct Scratch {
    float4 acc[2048];
    uint4 o[2][8][16][16][8];
    uint4 q[8][256];
    uint4 ml[2][8][16][2];
    unsigned int epoch[NCTA][32];
};
__device__ uint4 g_scratch[(sizeof(Scratch) + 32768) / 16];

struct Params {
    const char* wq[2];
    const char *x, *gw;
    Scratch* sc;
    unsigned short* out;
    const char* kv[4];
    CUtensorMap wo[2];
};

__device__ __forceinline__ void mbar_arrive(uint32_t bar) {
    asm volatile("mbarrier.arrive.shared::cta.b64 _, [%0];" ::"r"(bar) : "memory");
}
__device__ __forceinline__ void mbar_wait(uint32_t bar) {
    asm volatile("{\n.reg .pred p, q;\n.reg .u32 n;\nmov.u32 n, 0;\n"
                 "W:\nmbarrier.try_wait.parity.shared::cta.b64 p, [%0], 0;\nadd.u32 n, n, 1;\n"
                 "setp.lt.and.u32 q, n, %1, !p;\n@q bra W;\n}\n" ::"r"(bar), "n"(SPIN_LIMIT) : "memory");
}
__device__ __forceinline__ uint32_t now_ns() {
    uint32_t t;
    asm volatile("mov.u32 %0, %globaltimer_lo;" : "=r"(t));
    return t;
}
__device__ __forceinline__ void wait_time_or(uint32_t due, uint32_t bar) {
#pragma unroll 1
    for (uint32_t n = 0; n < SPIN_LIMIT; n++) {
        const uint32_t now = now_ns();
        uint32_t ok;
        asm volatile("{\n.reg .pred p;\nmbarrier.test_wait.parity.shared::cta.b64 p, [%1], 0;\nselp.u32 %0, 1, 0, p;\n}\n"
                     : "=r"(ok) : "r"(bar) : "memory");
        if ((int)(now - due) >= 0 || ok) break;
    }
}
__device__ __forceinline__ void ldsm4(uint32_t (&r)[4], uint32_t a) {
    asm volatile("ldmatrix.sync.aligned.m8n8.x4.shared.b16 {%0,%1,%2,%3}, [%4];"
                 : "=r"(r[0]), "=r"(r[1]), "=r"(r[2]), "=r"(r[3]) : "r"(a) : "memory");
}
__device__ __forceinline__ void ldsm4t(uint32_t (&r)[4], uint32_t a) {
    asm volatile("ldmatrix.sync.aligned.m8n8.x4.trans.shared.b16 {%0,%1,%2,%3}, [%4];"
                 : "=r"(r[0]), "=r"(r[1]), "=r"(r[2]), "=r"(r[3]) : "r"(a) : "memory");
}
__device__ __forceinline__ void mma16816(float (&c)[4], const uint32_t (&a)[4], uint32_t b0, uint32_t b1) {
    asm("mma.sync.aligned.m16n8k16.row.col.f32.bf16.bf16.f32 {%0,%1,%2,%3}, {%4,%5,%6,%7}, {%8,%9}, {%0,%1,%2,%3};"
        : "+f"(c[0]), "+f"(c[1]), "+f"(c[2]), "+f"(c[3])
        : "r"(a[0]), "r"(a[1]), "r"(a[2]), "r"(a[3]), "r"(b0), "r"(b1));
}
__device__ __forceinline__ float bf_lo(uint32_t v) { return __uint_as_float(v << 16); }
__device__ __forceinline__ float bf_hi(uint32_t v) { return __uint_as_float(v & 0xffff0000u); }
__device__ __forceinline__ uint32_t pack_bf2(float lo, float hi) {
    uint32_t r;
    asm("cvt.rn.bf16x2.f32 %0, %1, %2;" : "=r"(r) : "f"(hi), "f"(lo));
    return r;
}
__device__ __forceinline__ float round_bf(float v) { return __uint_as_float(pack_bf2(0.f, v)); }
__device__ __forceinline__ float ex2(float v) {
    float r;
    asm("ex2.approx.ftz.f32 %0, %1;" : "=f"(r) : "f"(v));
    return r;
}
__device__ __forceinline__ float rcp(float v) {
    float r;
    asm("rcp.approx.ftz.f32 %0, %1;" : "=f"(r) : "f"(v));
    return r;
}
__device__ __forceinline__ float shx(float v, int m) { return __shfl_xor_sync(0xffffffffu, v, m); }
__device__ __forceinline__ uint32_t tagged(float v, uint32_t tag) { return (__float_as_uint(v) & ~TAGM) | tag; }
__device__ __forceinline__ float untag(uint32_t v) { return __uint_as_float(v & ~TAGM); }
__device__ __forceinline__ void put2(void* p, uint32_t a, uint32_t b) {
    asm volatile("st.relaxed.gpu.global.v2.b32 [%0], {%1, %2};" ::"l"(p), "r"(a), "r"(b) : "memory");
}
template <int N>
__device__ __forceinline__ void gather(uint4 (&v)[N], const void* p, uint32_t tag) {
    uint32_t n = 0, bad;
    do {
        bad = 0;
#pragma unroll
        for (int k = 0; k < N; k++)
            asm volatile("ld.relaxed.gpu.global.v4.b32 {%0, %1, %2, %3}, [%4];"
                         : "=r"(v[k].x), "=r"(v[k].y), "=r"(v[k].z), "=r"(v[k].w) : "l"((const char*)p + 512 * k) : "memory");
#pragma unroll
        for (int k = 0; k < N; k++) bad |= (v[k].x ^ tag) | (v[k].y ^ tag) | (v[k].z ^ tag) | (v[k].w ^ tag);
    } while (__any_sync(0xffffffffu, bad & TAGM) && ++n < SPIN_LIMIT);
}
__device__ __forceinline__ uint64_t evict_first() {
    uint64_t pol;
    asm volatile("createpolicy.fractional.L2::evict_first.b64 %0, 1.0;" : "=l"(pol));
    return pol;
}

constexpr float SCALE_LOG2E = 0.0625f * 1.4426950408889634f;

__global__ void __launch_bounds__(NTHREADS, 1) gated_mix_decode_kernel(const __grid_constant__ Params p) {
    extern __shared__ __align__(1024) char smem[];
    asm volatile("prefetch.global.L2 [%0];" ::"l"(p.wq[0] + (size_t)(blockIdx.x * NTHREADS + threadIdx.x) * 32));
    uint32_t due = now_ns();
    const uint32_t sb = (uint32_t)__cvta_generic_to_shared(smem);
    const uint32_t bars = sb + OFF_BAR;
    const uint32_t tid = threadIdx.x, lane = tid & 31;
    const uint32_t cta = blockIdx.x, head = cta >> 4, j = cta & 15;
    const uint32_t mi = lane >> 3, r = lane & 7;

    if (tid < 224) {
        const uint64_t pol = evict_first();
        const char* src = p.wq[j >> 3] + ((tid >> 3) * (16 * 8192) + head * 1024 + (j & 7) * 128 + r * 16);
        uint32_t dst = sb + OFF_W + (tid >> 3) * (16 * 128) + 16 * (r ^ (2 * mi));
#pragma unroll 1
        for (int i = 0; i < 8; i++) {
            asm volatile("cp.async.cg.shared.global.L2::cache_hint [%0], [%1], 16, %2;"
                         ::"r"(dst), "l"(src), "l"(pol) : "memory");
            asm volatile("cp.async.cg.shared.global.L2::cache_hint [%0], [%1], 16, %2;"
                         ::"r"(dst ^ (128 + 16)), "l"(src + 8192), "l"(pol) : "memory");
            dst += 256;
            src += 16384;
        }
    }
    const uint32_t warp = __shfl_sync(0xffffffffu, tid >> 5, 0);
    const uint32_t g = lane >> 2, t = lane & 3;

    if (warp == 9) {
        char* const sc = (char*)p.sc;
        void* const qdst = sc + (uint32_t)(offsetof(Scratch, q) + cta * 256 + (t * 8 + g) * 8);
        uint32_t tag = p.sc->epoch[cta][0];
        tag = tag == 14 ? 1 : tag + 1;
        __syncwarp();
        p.sc->epoch[cta][0] = tag;
        *(uint32_t*)(smem + OFF_TAG) = tag;
        asm volatile("barrier.sync 2, 320;" ::: "memory");
        {
            float q0 = 0.f, q1 = 0.f;
#pragma unroll
            for (int w = 0; w < 7; w++) {
                const float2 f = *(const float2*)(smem + OFF_S + (w * 32 + lane) * 8);
                q0 += f.x; q1 += f.y;
            }
            put2(qdst, pack_bf2(0.f, q0) | tag, pack_bf2(0.f, q1) | tag);
            asm volatile("barrier.arrive 3, 288;" ::: "memory");
        }
        {
            float z = 0.f;
#pragma unroll 1
            for (uint32_t i = lane; i < DM / 4; i += 32) {
                const uint2 a = __ldg((const uint2*)p.x + i), b = __ldg((const uint2*)p.gw + i);
                uint32_t m0, m1;
                asm("mul.rn.bf16x2 %0, %1, %2;" : "=r"(m0) : "r"(a.x), "r"(b.x));
                asm("mul.rn.bf16x2 %0, %1, %2;" : "=r"(m1) : "r"(a.y), "r"(b.y));
                z += (bf_lo(m0) + bf_hi(m0)) + (bf_lo(m1) + bf_hi(m1));
            }
#pragma unroll 1
            for (int s = 16; s; s >>= 1) z += shx(z, s);
            const float gate = round_bf(rcp(1.f + ex2(round_bf(z) * -1.4426950408889634f)));
            *(float2*)(smem + OFF_TAG + 8) = make_float2(gate, round_bf(1.f - gate));
        }
#pragma unroll 1
        for (int br = 0; br < 2; br++) {
            mbar_wait(bars + 8 * (B_ML + br));
            float m = ((const float*)(smem + OFF_M))[br * 16 + (lane & 15)];
            float l = ((const float*)(smem + OFF_L))[br * 16 + (lane & 15)];
#pragma unroll
            for (int s = 1; s < 8; s <<= 1) { m = fmaxf(m, shx(m, s)); l += shx(l, s); }
            if (r == 0) put2(sc + (uint32_t)(offsetof(Scratch, ml) + br * 4096 + cta * 32 + lane), tagged(m, tag), tagged(l, tag));
        }
#pragma unroll 1
        for (int br = 0; br < 2; br++) {
            uint4 ml[1], v[4];
            gather<1>(ml, sc + (uint32_t)(offsetof(Scratch, ml) + br * 4096 + head * 512 + (lane & 15) * 32), tag);
            const float m = untag((lane & 16) ? ml[0].z : ml[0].x);
            float M = m;
#pragma unroll
            for (int s = 8; s; s >>= 1) M = fmaxf(M, shx(M, s));
            const float e = ex2((m - M) * SCALE_LOG2E);
            float L = e * untag((lane & 16) ? ml[0].w : ml[0].y);
#pragma unroll
            for (int s = 8; s; s >>= 1) L += shx(L, s);
            const float wgt = e * rcp(L);
            float wk[4];
#pragma unroll
            for (int k = 0; k < 4; k++) wk[k] = __shfl_sync(0xffffffffu, wgt, 4 * (lane & 4) + 4 * k + mi);
            if (br) {
                mbar_wait(bars + 8 * (B_FULL + OWAIT));
                wait_time_or(now_ns() + ODELAY, bars + 8 * (B_FULL + OWAIT + 1));
            }
            gather<4>(v, sc + (uint32_t)(offsetof(Scratch, o) + br * sizeof(Scratch::o[0]) + cta * 2048 + lane * 16), tag);
            float o0 = 0.f, o1 = 0.f, o2 = 0.f, o3 = 0.f;
#pragma unroll
            for (int k = 0; k < 4; k++) {
                o0 = fmaf(wk[k], untag(v[k].x), o0); o1 = fmaf(wk[k], untag(v[k].y), o1);
                o2 = fmaf(wk[k], untag(v[k].z), o2); o3 = fmaf(wk[k], untag(v[k].w), o3);
            }
            const bool h1 = lane & 8, h2 = lane & 16;
            const float b0 = (h1 ? o2 : o0) + shx(h1 ? o0 : o2, 8);
            const float b1 = (h1 ? o3 : o1) + shx(h1 ? o1 : o3, 8);
            const float od = (h2 ? b1 : b0) + shx(h2 ? b0 : b1, 16);
            const uint32_t d = 4 * (lane & 4) + 2 * t + ((lane >> 3) & 1) + ((lane & 16) >> 1);
            ((unsigned short*)(smem + OFF_O))[br * 32 + d] = (unsigned short)pack_bf2(od, 0.f);
            __syncwarp();
            if (lane == 0) mbar_arrive(bars + 8 * (B_OREADY + br));
        }
    } else if (warp == 8) {
        if (lane == 0) {
#pragma unroll 6
            for (int i = 0; i < NBAR1; i++) {
                asm volatile("mbarrier.init.shared::cta.b64 [%0], 1;" ::"r"(bars + 8 * i) : "memory");
                asm volatile("mbarrier.init.shared::cta.b64 [%0], 8;" ::"r"(bars + 8 * (NBAR1 + i)) : "memory");
            }
            asm volatile("fence.mbarrier_init.release.cluster;" ::: "memory");
        }
        __syncwarp();
        asm volatile("barrier.arrive 2, 320;" ::: "memory");
        if (lane == 0) {
            asm volatile("prefetch.tensormap [%0];" ::"l"(&p.wo[0]) : "memory");
            asm volatile("prefetch.tensormap [%0];" ::"l"(&p.wo[1]) : "memory");
            const uint64_t pol = evict_first();
            due += RATE0 + STAG * cta;
            uint32_t i = 0;
#pragma unroll 1
            for (int s = 0; s < 5; s++) {
                const bool kv = s < 4;
                const char* src = p.kv[s & 3] + (head * (SK * 512) + j * TILE);
                const uint32_t end = i + ((s & 2) ? NB : NA);
#pragma unroll 1
                for (; i < end; i++) {
                    const uint32_t full = bars + 8 * (B_FULL + i);
                    if (kv && i >= NS) mbar_wait(full + 8 * (B_EMPTY - NS));
                    if (i >= WIN) mbar_wait(full - 8 * (kv ? WIN : WINE));
                    wait_time_or(due, i >= WMIN ? full - 8 * WMIN : full);
                    asm volatile("mbarrier.arrive.expect_tx.shared::cta.b64 _, [%0], %1;" ::"r"(full), "r"(kv ? TILE : WOT) : "memory");
                    if (kv) {
                        asm volatile("cp.async.bulk.shared::cluster.global.mbarrier::complete_tx::bytes.L2::cache_hint [%0], [%1], %2, [%3], %4;"
                                     ::"r"(sb + OFF_RING + (i % NS) * TILE), "l"(src), "n"(TILE), "r"(full), "l"(pol) : "memory");
                        src += 16 * TILE;
                        due += RATE;
                    } else {
                        asm volatile("cp.async.bulk.tensor.2d.shared::cluster.global.mbarrier::complete_tx::bytes.L2::cache_hint [%0], [%1, {%2, %3}], [%4], %5;"
                                     ::"r"(sb + OFF_W + (i - NKV) * WOT), "l"(&p.wo[(i >> 1) & 1]), "r"(0),
                                       "r"((head * 32 + (i & 1) * 16 + j) * (WOT / 128)), "r"(full), "l"(pol) : "memory");
                        due += WORATE;
                    }
                }
            }
        }
        __syncwarp();
    } else {
        char* const sc = (char*)p.sc;
        char* odst = sc + (uint32_t)(offsetof(Scratch, o) + (head * 16 + 2 * warp + (t & 1)) * 2048 + j * 128 + ((t >> 1) * 8 + g) * 8);
        if (warp < 7) {
            uint32_t xb[8];
            asm volatile("ld.global.nc.v4.u32 {%0, %1, %2, %3}, [%8];\nld.global.nc.v4.u32 {%4, %5, %6, %7}, [%8 + 16];\n"
                         "cp.async.wait_all;"
                         : "=r"(xb[0]), "=r"(xb[1]), "=r"(xb[2]), "=r"(xb[3]), "=r"(xb[4]), "=r"(xb[5]), "=r"(xb[6]), "=r"(xb[7])
                         : "l"(p.x + (warp * 128 + t * 32)) : "memory");
            __syncwarp();
            const uint32_t a0 = sb + OFF_W + (warp * 64 + 16 * (r >> 1) + 2 * (mi >> 1) + (r & 1)) * 128 + 16 * ((mi & 1) ^ r);
            float c[4][4] = {};
#pragma unroll
            for (int ks = 0; ks < 4; ks++) {
#pragma unroll
                for (int i = 0; i < 4; i++) {
                    uint32_t a[4];
                    ldsm4t(a, (a0 ^ (32 * i)) + ks * 512);
                    mma16816(c[i], a, xb[2 * ks], xb[2 * ks + 1]);
                }
            }
            *(float2*)(smem + OFF_S + tid * 8) =
                make_float2((t & 2) ? ((t & 1) ? c[3][0] : c[2][0]) : ((t & 1) ? c[1][0] : c[0][0]),
                            (t & 2) ? ((t & 1) ? c[3][2] : c[2][2]) : ((t & 1) ? c[1][2] : c[0][2]));
        }
        asm volatile("barrier.sync 2, 320;" ::: "memory");
        asm volatile("fence.proxy.async.shared::cta;" ::: "memory");
        const uint32_t tag = *(const uint32_t*)(smem + OFF_TAG);
        char* const ap = sc + ((tid >> 6) * 8192 + (tid & 64) * 64 + ((tid >> 4) & 3) * 1024 + (tid & 8) * 32 + (tag & 1) * 128 + r * 16);
        if (cta == 0) *(float4*)((uintptr_t)ap ^ 128) = make_float4(0.f, 0.f, 0.f, 0.f);

        const bool valid = t == (g & 3);
        const uint32_t lm0 = sb + OFF_RING + (8 * (mi >> 1) + r) * 512 + 16 * ((mi & 1) ^ (r >> 1));
        const uint32_t lm1 = lm0 ^ 32;
        {
            mbar_wait(bars + 8 * (B_FULL + QWAIT));
            uint4 v[1];
            gather<1>(v, sc + (uint32_t)(offsetof(Scratch, q) + head * 4096 + tid * 16), tag);
            uint32_t* qs = (uint32_t*)(smem + OFF_Q + (warp >> 1) * QS + (warp & 1) * 256) + g * 8 + t;
            qs[0] = __byte_perm(v[0].x, v[0].z, 0x7632);
            qs[4] = __byte_perm(v[0].y, v[0].w, 0x7632);
            asm volatile("barrier.sync 3, 288;" ::: "memory");
        }
        uint32_t qa[16][4];
        {
            const uint32_t q0 = sb + OFF_Q + ((mi & 1) * 2 + (r >> 2)) * QS + 16 * ((mi >> 1) ^ (r & 3));
#pragma unroll
            for (int k = 0; k < 16; k++) ldsm4(qa[k], (q0 ^ ((k & 1) * 32)) + 64 * (k >> 1));
        }
        uint32_t T0 = 0;
#pragma unroll 1
        for (int br = 0; br < 2; br++) {
            const uint32_t nt = br ? NB : NA;
            float mx = -INFINITY;
#pragma unroll 1
            for (uint32_t kt = warp >> 1; kt < nt; kt += 4) {
                const uint32_t T = T0 + kt, off = (T % NS) * TILE + (warp & 1) * 8192;
                mbar_wait(bars + 8 * (B_FULL + T));
                float c0[4] = {0.f, 0.f, 0.f, 0.f}, c1[4] = {0.f, 0.f, 0.f, 0.f};
#pragma unroll
                for (int k = 0; k < 16; k++) {
                    uint32_t b[4];
                    ldsm4(b, ((k & 1) ? lm1 : lm0) + off + 64 * (k >> 1));
                    mma16816(c0, qa[k], b[0], b[1]);
                    mma16816(c1, qa[k], b[2], b[3]);
                }
                __syncwarp();
                if (lane == 0) asm volatile("mbarrier.arrive.shared::cta.b64 _, [%0], 4;" ::"r"(bars + 8 * (B_EMPTY + T)) : "memory");
                float4 s;
                s.x = round_bf(br ? c0[2] : c0[0]); s.y = round_bf(br ? c0[3] : c0[1]);
                s.z = round_bf(br ? c1[2] : c1[0]); s.w = round_bf(br ? c1[3] : c1[1]);
                if (valid) *(float4*)(smem + OFF_S + ((2 * kt + (warp & 1)) * 8 + g) * 16) = s;
                mx = fmaxf(fmaxf(mx, fmaxf(s.x, s.y)), fmaxf(s.z, s.w));
            }
            mx = fmaxf(mx, shx(mx, 5));
            mx = fmaxf(mx, shx(mx, 10));
            float* mred = (float*)(smem + OFF_M) + br * 16;
            if ((lane & 15) == 0) mred[(lane >> 1) + warp] = mx;
            asm volatile("barrier.sync 1, 256;" ::: "memory");
            {
                const float4 m0 = *(const float4*)(mred + (lane & 4) * 2), m1 = *(const float4*)(mred + (lane & 4) * 2 + 4);
                const float M = fmaxf(fmaxf(fmaxf(m0.x, m0.y), fmaxf(m0.z, m0.w)), fmaxf(fmaxf(m1.x, m1.y), fmaxf(m1.z, m1.w)));
                const float4 s = *(const float4*)(smem + OFF_S + tid * 16);
                const uint32_t p0 = pack_bf2(ex2((s.x - M) * SCALE_LOG2E), ex2((s.y - M) * SCALE_LOG2E));
                const uint32_t p1 = pack_bf2(ex2((s.z - M) * SCALE_LOG2E), ex2((s.w - M) * SCALE_LOG2E));
                *(uint2*)(smem + OFF_P + ((tid >> 4) * 8 + r) * 16 + (tid & 8)) = make_uint2(p0, p1);
                float l = (bf_lo(p0) + bf_hi(p0)) + (bf_lo(p1) + bf_hi(p1));
                l += shx(l, 1); l += shx(l, 2); l += shx(l, 8); l += shx(l, 16);
                if ((lane & ~4) == 0) mred[(OFF_L - OFF_M) / 4 + lane * 2 + warp] = tid < nt * 16 ? l : 0.f;
            }
            asm volatile("barrier.sync 1, 256;" ::: "memory");
            if (tid == 0) mbar_arrive(bars + 8 * (B_ML + br));
            T0 += nt;
            float o0[4] = {0.f, 0.f, 0.f, 0.f}, o1[4] = {0.f, 0.f, 0.f, 0.f};
#pragma unroll 1
            for (uint32_t vt = 0; vt < nt; vt++) {
                const uint32_t T = T0 + vt, off = (T % NS) * TILE + warp * 64;
                uint4 pb = make_uint4(0u, 0u, 0u, 0u);
                if (valid) pb = *(const uint4*)(smem + OFF_P + (vt * 8 + g) * 16);
                mbar_wait(bars + 8 * (B_FULL + T));
                uint32_t a[4][4];
                ldsm4t(a[0], lm0 + off);
                ldsm4t(a[1], lm1 + off);
                ldsm4t(a[2], lm0 + off + 8192);
                ldsm4t(a[3], lm1 + off + 8192);
                mma16816(o0, a[0], pb.x, pb.y);
                mma16816(o1, a[1], pb.x, pb.y);
                mma16816(o0, a[2], pb.z, pb.w);
                mma16816(o1, a[3], pb.z, pb.w);
                __syncwarp();
                if (lane == 0) mbar_arrive(bars + 8 * (B_EMPTY + T));
            }
            T0 += nt;
            const float u0 = o0[0] + o0[3] + shx(o1[0] + o1[3], 1);
            const float u1 = o0[2] + o0[1] + shx(o1[2] + o1[1], 1);
            put2(odst, tagged(u0, tag), tagged(u1, tag));
            odst += sizeof(Scratch::o[0]);
        }
        if (warp < 7) {
            uint32_t wm = sb + OFF_W + (8 * (mi >> 1) + r) * (DM * 2) + 128 * warp + 16 * ((mi & 1) ^ ((warp - r) & 7));
            unsigned short* op = p.out + (64 * warp + 16 * t + g);
            float y0 = 0.f, y1 = 0.f;
#pragma unroll 1
            for (int br = 0; br < 2; br++) {
                uint32_t ob[4], a[4][4];
                float c[4][4] = {};
                mbar_wait(bars + 8 * (B_FULL + NKV + 2 * br));
#pragma unroll
                for (int i = 0; i < 4; i++) ldsm4t(a[i], wm ^ (32 * i));
                mbar_wait(bars + 8 * (B_OREADY + br));
                const float gb = *(const float*)(smem + OFF_TAG + 8 + 4 * br);
#pragma unroll
                for (int i = 0; i < 4; i++) ob[i] = ((const uint32_t*)(smem + OFF_O))[br * 16 + 4 * i + t];
#pragma unroll
                for (int i = 0; i < 4; i++) mma16816(c[i], a[i], ob[0], ob[1]);
                asm volatile("" : "+f"(c[0][0]), "+f"(c[1][0]), "+f"(c[2][0]), "+f"(c[3][0]));
                mbar_wait(bars + 8 * (B_FULL + NKV + 2 * br + 1));
#pragma unroll
                for (int i = 0; i < 4; i++) ldsm4t(a[i], (wm ^ (32 * i)) + WOT);
#pragma unroll
                for (int i = 0; i < 4; i++) mma16816(c[i], a[i], ob[2], ob[3]);
                y0 = fmaf(gb, (t & 2) ? ((t & 1) ? c[3][0] : c[2][0]) : ((t & 1) ? c[1][0] : c[0][0]), y0);
                y1 = fmaf(gb, (t & 2) ? ((t & 1) ? c[3][2] : c[2][2]) : ((t & 1) ? c[1][2] : c[0][2]), y1);
                wm += 2 * WOT;
                asm volatile("{\n.reg .pred l, p, q;\n.reg .f32 n0, s0, s1, n1;\n.reg .b16 lo, hi;\n.reg .b32 w;\n"
                             "setp.ne.u32 l, %6, 0;\n"
                             "@l atom.relaxed.gpu.global.add.v4.f32 {n0, s0, s1, n1}, [%0], {%4, %2, %3, %4};\n"
                             "add.f32 s0, s0, %2;\nadd.f32 s1, s1, %3;\ncvt.rn.bf16x2.f32 w, s1, s0;\nmov.b32 {lo, hi}, w;\n"
                             "setp.eq.and.f32 p, n0, %5, l;\nsetp.eq.and.f32 q, n1, %5, l;\n"
                             "@p st.global.b16 [%1], lo;\n@q st.global.b16 [%1 + 16], hi;\n@l exit;\n}\n"
                             ::"l"(ap), "l"(op), "f"(y0), "f"(y1), "f"(1.f), "f"((float)(NCTA - 1)), "r"(br) : "memory");
            }
        }
    }
}

}

extern "C" void kernel_launch(void* const* d_in, const int* in_sizes, int n_in, void* d_out, int out_size) {
    (void)in_sizes; (void)n_in; (void)out_size;
    Params p;
    p.wq[0] = (const char*)d_in[3];
    p.wq[1] = (const char*)d_in[8];
    p.x = (const char*)d_in[0];
    p.gw = (const char*)d_in[10];
    p.kv[0] = (const char*)d_in[1] + (size_t)(SK - WA) * 512;
    p.kv[1] = (const char*)d_in[2] + (size_t)(SK - WA) * 512;
    p.kv[2] = (const char*)d_in[6];
    p.kv[3] = (const char*)d_in[7];
    p.out = (unsigned short*)d_out;
    void* sc = nullptr;
    cudaGetSymbolAddress(&sc, g_scratch);
    p.sc = (Scratch*)(((uintptr_t)sc + 32767) & ~(uintptr_t)32767);
    typedef CUresult (*EncodeFn)(CUtensorMap*, CUtensorMapDataType, cuuint32_t, void*, const cuuint64_t*, const cuuint64_t*,
                                 const cuuint32_t*, const cuuint32_t*, CUtensorMapInterleave, CUtensorMapSwizzle,
                                 CUtensorMapL2promotion, CUtensorMapFloatOOBfill);
    void* fn = nullptr;
    cudaDriverEntryPointQueryResult qr;
    cudaGetDriverEntryPoint("cuTensorMapEncodeTiled", &fn, cudaEnableDefault, &qr);
    for (int b = 0; b < 2; b++) {
        const cuuint64_t dims[2] = {64, 4096 * 7}, strides[1] = {128};
        const cuuint32_t box[2] = {64, WOT / 128}, es[2] = {1, 1};
        ((EncodeFn)fn)(&p.wo[b], CU_TENSOR_MAP_DATA_TYPE_BFLOAT16, 2, d_in[b ? 9 : 4], dims, strides, box, es,
                       CU_TENSOR_MAP_INTERLEAVE_NONE, CU_TENSOR_MAP_SWIZZLE_128B, CU_TENSOR_MAP_L2_PROMOTION_NONE,
                       CU_TENSOR_MAP_FLOAT_OOB_FILL_NONE);
    }
    cudaFuncSetAttribute(gated_mix_decode_kernel, cudaFuncAttributeMaxDynamicSharedMemorySize, SMEM_BYTES);
    gated_mix_decode_kernel<<<NCTA, NTHREADS, SMEM_BYTES>>>(p);
}
```
